```python
import torch

def _softmax(x, axis=-1):
    return torch.softmax(x, dim=axis)

def _gelu(x):
    return torch.nn.functional.gelu(x, approximate='tanh')

def _silu(x):
    return torch.nn.functional.silu(x)

def _sigmoid(x):
    return torch.sigmoid(x)

def _layernorm(x, axis=-1, eps=1e-05):
    m = x.mean(dim=axis, keepdim=True)
    v = x.var(dim=axis, keepdim=True, unbiased=False)
    return (x - m) / torch.sqrt(v + eps)

def _scatter_add(tgt, idx, src, axis=0):
    return tgt.clone().index_add_(axis, idx, src)

def _segment_sum(src, seg, n):
    out = torch.zeros((n,) + src.shape[1:], dtype=src.dtype)
    return out.index_add_(0, seg, src)

def _pad(x, pw):
    flat = tuple((v for pair in reversed(pw) for v in pair))
    return torch.nn.functional.pad(x, flat)
kernel_name = 'gated_mix__memory_aug_recurrent_mem_tr__linear_attn_block__prompt'

def setup_inputs():

    _w = lambda a: (lambda t: t.to(torch.bfloat16) if t.is_floating_point() else t)(torch.as_tensor(a))

    def _A_setup():
        B, S, Dm = (1, 2048, 512)
        H, Dh = (32, 128)
        M, seg = (8, 32)
        seg = min(seg, S)
        S = S // seg * seg
        return {'x': _w((lambda *s: torch.randn(*s, dtype=torch.bfloat16) * 0.05)(B, S, Dm)), 'mem0': _w((lambda *s: torch.randn(*s, dtype=torch.bfloat16) * 0.8)(B, M, Dm)), 'Wq': _w((lambda *s: torch.randn(*s, dtype=torch.bfloat16) * 1.6)(Dm, H, Dh) * Dm ** (-0.5)), 'Wk': _w((lambda *s: torch.randn(*s, dtype=torch.bfloat16) * 1.6)(Dm, H, Dh) * Dm ** (-0.5)), 'Wv': _w((lambda *s: torch.randn(*s, dtype=torch.bfloat16) * 0.8)(Dm, H, Dh) * Dm ** (-0.5)), 'Wo': _w((lambda *s: torch.randn(*s, dtype=torch.bfloat16) * 0.8)(H, Dh, Dm) * (H * Dh) ** (-0.5)), 'seg_len': seg}
    _A_in = _A_setup()

    def _B_setup():
        B, S, D = (1, 2048, 512)
        return {'x': _w((lambda *s: torch.randn(*s, dtype=torch.bfloat16) * 0.05)(B, S, D)), 'wqkv': _w((lambda *s: torch.randn(*s, dtype=torch.bfloat16) * 1.6)(D, 3 * D)), 'wo': _w((lambda *s: torch.randn(*s, dtype=torch.bfloat16) * 0.1)(D, D))}
    _B_in = _B_setup()
    return {'A_x': _A_in['x'], 'A_mem0': _A_in['mem0'], 'A_Wq': _A_in['Wq'], 'A_Wk': _A_in['Wk'], 'A_Wv': _A_in['Wv'], 'A_Wo': _A_in['Wo'], 'A_seg_len': _A_in['seg_len'], 'B_x': _B_in['x'], 'B_wqkv': _B_in['wqkv'], 'B_wo': _B_in['wo'], 'gate_w': _w((lambda *s: torch.randn(*s, dtype=torch.bfloat16) * 0.05)(512) * 16.0)}

def reference(A_x, A_mem0, A_Wq, A_Wk, A_Wv, A_Wo, A_seg_len, B_x, B_wqkv, B_wo, gate_w):

    def _A_ref(x, mem0, Wq, Wk, Wv, Wo, seg_len):
        B, S, Dm = x.shape
        H, Dh = (Wq.shape[1], Wq.shape[2])
        M = mem0.shape[1]
        scale = Dh ** (-0.5)
        n_seg = S // seg_len
        L = M + seg_len
        idx = torch.arange(L)
        mask = (idx[:, None] < M) | (idx[:, None] >= idx[None, :])
        mem = mem0
        outs = []
        for s in range(n_seg):
            xs = x[:, s * seg_len:(s + 1) * seg_len, :].clone()
            h = torch.concatenate([mem, xs], axis=1)
            q = torch.einsum('btd,dhe->bhte', h, Wq)
            k = torch.einsum('btd,dhe->bhte', h, Wk)
            v = torch.einsum('btd,dhe->bhte', h, Wv)
            scores = torch.einsum('bhqe,bhke->bhqk', q, k) * scale
            scores = torch.where(mask[None, None], scores, -1000000000.0)
            p = _softmax(scores, axis=-1)
            o = torch.einsum('bhqk,bhke->bhqe', p, v)
            o = torch.einsum('bhte,hed->btd', o, Wo)
            mem = o[:, :M, :].clone()
            outs.append(o[:, M:, :])
        return torch.concatenate(outs, axis=1)

    def _B_ref(x, wqkv, wo):
        B, S, D = x.shape
        H = 32
        Dh = D // H
        qkv = (lambda x, *d: x.permute(*d))((x @ wqkv).reshape(B, S, 3, H, Dh), 2, 0, 3, 1, 4)
        q, k, v = (qkv[0], qkv[1], qkv[2])
        phi = lambda t: torch.where(t > 0, t + 1, torch.exp(t)) + 1e-06
        pq, pk = (phi(q), phi(k))
        kv = torch.einsum('bhsd,bhse->bhde', pk, v)
        z = torch.einsum('bhsd->bhd', pk)
        num = torch.einsum('bhqd,bhde->bhqe', pq, kv)
        den = torch.einsum('bhqd,bhd->bhq', pq, z)[..., None] + 1e-06
        o = num / den
        return (lambda x, *d: x.permute(*d))(o, 0, 2, 1, 3).reshape(B, S, D) @ wo
    x = A_x
    g = _sigmoid((x * gate_w).sum(-1, keepdims=True))
    a = _A_ref(x, A_mem0, A_Wq, A_Wk, A_Wv, A_Wo, A_seg_len)
    b = _B_ref(x, B_wqkv, B_wo)
    return g * a + (1 - g) * b
```

```cpp
#include <cuda_runtime.h>
#include <cuda.h>
#include <cuda_bf16.h>
#include <cuda_fp16.h>
#include <stdint.h>

typedef __nv_bfloat16 bf16;

constexpr int NTOK = 2048, DM = 512, NH = 32, DH = 128, NSEG = 64, SEG = 32, NMEM = 8;
constexpr int HD = NH * DH;
constexpr int NREC = 64;

__device__ __align__(1024) bf16 gK[NSEG * NH * SEG * DH];
__device__ __align__(1024) bf16 gV[NSEG * NH * SEG * DH];
__device__ __align__(1024) bf16 gKm[NSEG * NH * NMEM * DH];
__device__ __align__(1024) bf16 gVm[NSEG * NH * NMEM * DH];
__device__ uint4 gAccRaw[(2 << 20) / 16];
__device__ __align__(256) unsigned gTime[NSEG * NREC];
constexpr int NT64 = NTOK / 64, NKB = 72;
__device__ __align__(1024) bf16 gA[NT64 * NKB * 4096];
__device__ __align__(1024) bf16 gP[9 * NT64 * 4 * 8192];
__device__ float gG[NTOK];
__device__ __align__(16) float gKVp[8 * 16 * 1024];
__device__ float gZp[8 * 16 * 256];
constexpr int F_BAR = 0, F_B = 64, F_PH = 96, F_P = 128, F_O = 256, F_KV = 768, F_M = F_KV + 1024, F_W = F_M + 2048, F_X = F_W + 64, F_END = 4224;
__device__ __align__(128) unsigned gFlags[2 * F_END];
__device__ unsigned gEpoch;

__device__ __forceinline__ uint32_t s2u(const void* p) { return (uint32_t)__cvta_generic_to_shared(p); }
__device__ __forceinline__ uint32_t mapa(uint32_t a, uint32_t r) {
    uint32_t o; asm("mapa.shared::cluster.u32 %0, %1, %2;" : "=r"(o) : "r"(a), "r"(r)); return o;
}
__device__ __forceinline__ void cluster_sync() {
    asm volatile("barrier.cluster.arrive.release.aligned; barrier.cluster.wait.acquire.aligned;" ::: "memory");
}
__device__ __forceinline__ void bar_sync(int id, int n) { asm volatile("bar.sync %0, %1;" :: "r"(id), "r"(n) : "memory"); }
__device__ __forceinline__ void bar_arrive(int id, int n) { asm volatile("bar.arrive %0, %1;" :: "r"(id), "r"(n) : "memory"); }
__device__ __forceinline__ void mbar_init(uint32_t b, uint32_t n) { asm volatile("mbarrier.init.shared::cta.b64 [%0], %1;" :: "r"(b), "r"(n) : "memory"); }
__device__ __forceinline__ void mbar_arrive(uint32_t b) { asm volatile("mbarrier.arrive.shared::cta.b64 _, [%0];" :: "r"(b) : "memory"); }
__device__ __forceinline__ void mbar_arrive_tx(uint32_t b, uint32_t tx) {
    asm volatile("mbarrier.arrive.expect_tx.shared::cta.b64 _, [%0], %1;" :: "r"(b), "r"(tx) : "memory");
}
__device__ __forceinline__ bool mbar_try(uint32_t b, uint32_t par) {
    uint32_t ok;
    asm volatile("{ .reg .pred p; mbarrier.try_wait.parity.shared::cta.b64 p, [%1], %2; selp.u32 %0, 1, 0, p; }"
                 : "=r"(ok) : "r"(b), "r"(par) : "memory");
    return ok;
}
__device__ __forceinline__ void mbar_wait(uint32_t b, uint32_t par) {
    asm volatile("{\n.reg .pred p;\n.reg .u32 c;\nmov.u32 c, 512;\n"
                 "L_%=:\nmbarrier.try_wait.parity.shared::cta.b64 p, [%0], %1;\n@p bra.uni D_%=;\n"
                 "add.u32 c, c, -1;\nsetp.ne.u32 p, c, 0;\n@p bra.uni L_%=;\nD_%=:\n}"
                 :: "r"(b), "r"(par) : "memory");
}
__device__ __forceinline__ uint32_t mbar_gate(uint32_t b, uint32_t par, uint32_t v) {
    uint32_t r;
    asm volatile("{ .reg .pred p; mbarrier.try_wait.parity.shared::cta.b64 p, [%1], %2; selp.u32 %0, %3, %4, p; }"
                 : "=r"(r) : "r"(b), "r"(par), "r"(v), "r"(v ^ 16u) : "memory");
    return r;
}
__device__ __forceinline__ void st_async2(uint32_t a, uint32_t x, uint32_t y, uint32_t bar) {
    asm volatile("st.async.weak.shared::cluster.mbarrier::complete_tx::bytes.v2.b32 [%0], {%1,%2}, [%3];"
                 :: "r"(a), "r"(x), "r"(y), "r"(bar) : "memory");
}
__device__ __forceinline__ void st_async4(uint32_t a, float x, float y, float z, float w, uint32_t bar) {
    asm volatile("st.async.weak.shared::cluster.mbarrier::complete_tx::bytes.v4.f32 [%0], {%1,%2,%3,%4}, [%5];"
                 :: "r"(a), "f"(x), "f"(y), "f"(z), "f"(w), "r"(bar) : "memory");
}
__device__ __forceinline__ void cp_async16(uint32_t s, const void* g) {
    asm volatile("cp.async.cg.shared.global [%0], [%1], 16;" :: "r"(s), "l"(g) : "memory");
}
__device__ __forceinline__ void cp_async_commit() { asm volatile("cp.async.commit_group;" ::: "memory"); }
__device__ __forceinline__ void cp_async_wait_all() { asm volatile("cp.async.wait_all;" ::: "memory"); }
__device__ __forceinline__ void ldsm4(uint32_t (&r)[4], uint32_t a) {
    asm volatile("ldmatrix.sync.aligned.m8n8.x4.shared.b16 {%0,%1,%2,%3}, [%4];"
                 : "=r"(r[0]), "=r"(r[1]), "=r"(r[2]), "=r"(r[3]) : "r"(a) : "memory");
}
__device__ __forceinline__ void ldsm4t(uint32_t (&r)[4], uint32_t a) {
    asm volatile("ldmatrix.sync.aligned.m8n8.x4.trans.shared.b16 {%0,%1,%2,%3}, [%4];"
                 : "=r"(r[0]), "=r"(r[1]), "=r"(r[2]), "=r"(r[3]) : "r"(a) : "memory");
}
__device__ __forceinline__ void stsm4(uint32_t a, uint32_t r0, uint32_t r1, uint32_t r2, uint32_t r3) {
    asm volatile("stmatrix.sync.aligned.m8n8.x4.shared.b16 [%0], {%1,%2,%3,%4};"
                 :: "r"(a), "r"(r0), "r"(r1), "r"(r2), "r"(r3) : "memory");
}
__device__ __forceinline__ void stsm4t(uint32_t a, uint32_t r0, uint32_t r1, uint32_t r2, uint32_t r3) {
    asm volatile("stmatrix.sync.aligned.m8n8.x4.trans.shared.b16 [%0], {%1,%2,%3,%4};"
                 :: "r"(a), "r"(r0), "r"(r1), "r"(r2), "r"(r3) : "memory");
}
__device__ __forceinline__ void stsm2(uint32_t a, uint32_t r0, uint32_t r1) {
    asm volatile("stmatrix.sync.aligned.m8n8.x2.shared.b16 [%0], {%1,%2};" :: "r"(a), "r"(r0), "r"(r1) : "memory");
}
__device__ __forceinline__ void stsm2t(uint32_t a, uint32_t r0, uint32_t r1) {
    asm volatile("stmatrix.sync.aligned.m8n8.x2.trans.shared.b16 [%0], {%1,%2};" :: "r"(a), "r"(r0), "r"(r1) : "memory");
}
__device__ __forceinline__ uint32_t movm(uint32_t a) {
    uint32_t d; asm volatile("movmatrix.sync.aligned.m8n8.trans.b16 %0, %1;" : "=r"(d) : "r"(a)); return d;
}
__device__ __forceinline__ void mma(float (&d)[4], uint32_t a0, uint32_t a1, uint32_t a2, uint32_t a3, uint32_t b0, uint32_t b1) {
    asm volatile("mma.sync.aligned.m16n8k16.row.col.f32.bf16.bf16.f32 {%0,%1,%2,%3}, {%4,%5,%6,%7}, {%8,%9}, {%0,%1,%2,%3};"
                 : "+f"(d[0]), "+f"(d[1]), "+f"(d[2]), "+f"(d[3]) : "r"(a0), "r"(a1), "r"(a2), "r"(a3), "r"(b0), "r"(b1));
}
__device__ __forceinline__ void mma0(float (&d)[4], uint32_t a0, uint32_t a1, uint32_t a2, uint32_t a3, uint32_t b0, uint32_t b1) {
    asm volatile("mma.sync.aligned.m16n8k16.row.col.f32.bf16.bf16.f32 {%0,%1,%2,%3}, {%4,%5,%6,%7}, {%8,%9}, {%10,%10,%10,%10};"
                 : "=f"(d[0]), "=f"(d[1]), "=f"(d[2]), "=f"(d[3]) : "r"(a0), "r"(a1), "r"(a2), "r"(a3), "r"(b0), "r"(b1), "f"(0.f));
}
__device__ __forceinline__ uint32_t pack_bf(float lo, float hi) {
    uint32_t r; asm("cvt.rn.bf16x2.f32 %0, %1, %2;" : "=r"(r) : "f"(hi), "f"(lo)); return r;
}
__device__ __forceinline__ uint32_t pack_h(float lo, float hi) {
    uint32_t r; asm("cvt.rn.f16x2.f32 %0, %1, %2;" : "=r"(r) : "f"(hi), "f"(lo)); return r;
}
__device__ __forceinline__ uint32_t h2_to_bf2(uint32_t w) {
    float2 f = __half22float2(*reinterpret_cast<__half2*>(&w));
    return pack_bf(f.x, f.y);
}
__device__ __forceinline__ float ex2(float x) { float y; asm("ex2.approx.ftz.f32 %0, %1;" : "=f"(y) : "f"(x)); return y; }
__device__ __forceinline__ float rcp(float x) { float y; asm("rcp.approx.ftz.f32 %0, %1;" : "=f"(y) : "f"(x)); return y; }
__device__ __forceinline__ void sts32(uint32_t a, uint32_t x) { asm volatile("st.shared.b32 [%0], %1;" :: "r"(a), "r"(x) : "memory"); }
__device__ __forceinline__ void sts128(uint32_t a, float x, float y, float z, float w) {
    asm volatile("st.shared.v4.f32 [%0], {%1,%2,%3,%4};" :: "r"(a), "f"(x), "f"(y), "f"(z), "f"(w) : "memory");
}
__device__ __forceinline__ void sts64(uint32_t a, uint32_t x, uint32_t y) {
    asm volatile("st.shared.v2.b32 [%0], {%1,%2};" :: "r"(a), "r"(x), "r"(y) : "memory");
}
__device__ __forceinline__ float4 lds128f(uint32_t a) {
    float4 v; asm volatile("ld.shared.v4.f32 {%0,%1,%2,%3}, [%4];" : "=f"(v.x), "=f"(v.y), "=f"(v.z), "=f"(v.w) : "r"(a) : "memory"); return v;
}
__device__ __forceinline__ uint4 lds128(uint32_t a) {
    uint4 v; asm volatile("ld.shared.v4.b32 {%0,%1,%2,%3}, [%4];" : "=r"(v.x), "=r"(v.y), "=r"(v.z), "=r"(v.w) : "r"(a) : "memory"); return v;
}
__device__ __forceinline__ float2 lds64f(uint32_t a) {
    float2 v; asm volatile("ld.shared.v2.f32 {%0,%1}, [%2];" : "=f"(v.x), "=f"(v.y) : "r"(a) : "memory"); return v;
}
__device__ __forceinline__ uint2 lds64(uint32_t a) {
    uint2 v; asm volatile("ld.shared.v2.b32 {%0,%1}, [%2];" : "=r"(v.x), "=r"(v.y) : "r"(a) : "memory"); return v;
}
__device__ __forceinline__ float lds32f(uint32_t a) {
    float v; asm volatile("ld.shared.f32 %0, [%1];" : "=f"(v) : "r"(a) : "memory"); return v;
}
__device__ __forceinline__ uint4 ld_rlx4(const void* p) {
    uint4 v; asm volatile("ld.relaxed.gpu.global.v4.u32 {%0,%1,%2,%3}, [%4];" : "=r"(v.x), "=r"(v.y), "=r"(v.z), "=r"(v.w) : "l"(p) : "memory"); return v;
}
__device__ __forceinline__ uint32_t ld_rlx1(const void* p) {
    uint32_t v; asm volatile("ld.relaxed.gpu.global.u32 %0, [%1];" : "=r"(v) : "l"(p) : "memory"); return v;
}
__device__ __forceinline__ uint2 ld_rlx2(const void* p) {
    uint2 v; asm volatile("ld.relaxed.gpu.global.v2.u32 {%0,%1}, [%2];" : "=r"(v.x), "=r"(v.y) : "l"(p) : "memory"); return v;
}
__device__ __forceinline__ uint32_t clk32_after(uint32_t dep) {
    uint32_t c;
    asm volatile("{ .reg .pred p; setp.eq.u32 p, %1, 0xffffffff; @p trap; mov.u32 %0, %%clock; }" : "=r"(c) : "r"(dep) : "memory");
    return c;
}
__device__ __forceinline__ void st_rlx1(const void* p, uint32_t v) { asm volatile("st.relaxed.gpu.global.u32 [%0], %1;" :: "l"(p), "r"(v) : "memory"); }
__device__ __forceinline__ uint32_t gtime32() { uint32_t t; asm volatile("mov.u32 %0, %%globaltimer_lo;" : "=r"(t)); return t; }
__device__ __forceinline__ uint32_t ld_acq(const void* p) {
    uint32_t v; asm volatile("ld.acquire.gpu.global.u32 %0, [%1];" : "=r"(v) : "l"(p) : "memory"); return v;
}
__device__ __forceinline__ void st_rlx4(void* p, uint32_t v) {
    asm volatile("st.relaxed.gpu.global.v4.u32 [%0], {%1,%1,%1,%1};" :: "l"(p), "r"(v) : "memory");
}
__device__ __forceinline__ void red_h8(void* p, uint32_t a, uint32_t b, uint32_t c, uint32_t d) {
    asm volatile("red.relaxed.gpu.global.add.noftz.v4.f16x2 [%0], {%1,%2,%3,%4};" :: "l"(p), "r"(a), "r"(b), "r"(c), "r"(d) : "memory");
}
__device__ __forceinline__ void red_h2(void* p, uint32_t a) {
    asm volatile("red.relaxed.gpu.global.add.noftz.f16x2 [%0], %1;" :: "l"(p), "r"(a) : "memory");
}
__device__ __forceinline__ void red_rel(unsigned* p, unsigned v) {
    asm volatile("red.release.gpu.global.add.u32 [%0], %1;" :: "l"(p), "r"(v) : "memory");
}
__device__ __forceinline__ void red_rlx(unsigned* p, unsigned v) {
    asm volatile("red.relaxed.gpu.global.add.u32 [%0], %1;" :: "l"(p), "r"(v) : "memory");
}
__device__ __forceinline__ void wait_flag(const unsigned* p, unsigned n) {
#pragma unroll 1
    for (int it = 0; it < (1 << 13); it++) {
        if (__all_sync(~0u, ld_acq(p) >= n)) break;
    }
}
__device__ __forceinline__ void bulk_g2s(uint32_t dst, const void* src, uint32_t bytes, uint32_t bar) {
    asm volatile("cp.async.bulk.shared::cluster.global.mbarrier::complete_tx::bytes [%0], [%1], %2, [%3];"
                 :: "r"(dst), "l"(src), "r"(bytes), "r"(bar) : "memory");
}
__device__ __forceinline__ void tma2d(uint32_t dst, const CUtensorMap* m, int c0, int c1, uint32_t bar) {
    asm volatile("cp.async.bulk.tensor.2d.shared::cluster.global.mbarrier::complete_tx::bytes [%0], [%1, {%2, %3}], [%4];"
                 :: "r"(dst), "l"(m), "r"(c0), "r"(c1), "r"(bar) : "memory");
}
__device__ __forceinline__ float bf_lo(uint32_t w) { return __uint_as_float(w << 16); }
__device__ __forceinline__ float bf_hi(uint32_t w) { return __uint_as_float(w & 0xffff0000u); }
struct Maps { CUtensorMap x, wq, wk, wv, wo, wb, wo2; const bf16 *pq, *pk, *pv, *po, *pb, *po2; };
__host__ __device__ __forceinline__ int km_off(int r, int d) { return (d >> 6) * 512 + r * 64 + ((((d >> 3) & 7) ^ r) << 3) + (d & 7); }
__device__ __forceinline__ uint32_t clk32() { uint32_t c; asm volatile("{ .reg .u64 t; mov.u64 t, %%clock64; cvt.u32.u64 %0, t; }" : "=r"(c)); return c; }

#define ELECT "{\n.reg .pred p;\nelect.sync _|p, 0xffffffff;\n"
__device__ __forceinline__ void e_arrive(uint32_t bar) { asm volatile(ELECT "@p mbarrier.arrive.shared::cta.b64 _, [%0];\n}" :: "r"(bar) : "memory"); }
__device__ __forceinline__ void e_expect(uint32_t bar, uint32_t tx) {
    asm volatile(ELECT "@p mbarrier.arrive.expect_tx.shared::cta.b64 _, [%0], %1;\n}" :: "r"(bar), "r"(tx) : "memory");
}
__device__ __forceinline__ void e_tma2d(uint32_t dst, const CUtensorMap* m, int c0, int c1, uint32_t bar) {
    asm volatile(ELECT "@p cp.async.bulk.tensor.2d.shared::cluster.global.mbarrier::complete_tx::bytes [%0], [%1, {%2, %3}], [%4];\n}"
                 :: "r"(dst), "l"(m), "r"(c0), "r"(c1), "r"(bar) : "memory");
}
__device__ __forceinline__ void e_g2s(uint32_t dst, const void* src, uint32_t bytes, uint32_t bar) {
    asm volatile(ELECT "@p cp.async.bulk.shared::cluster.global.mbarrier::complete_tx::bytes [%0], [%1], %2, [%3];\n}"
                 :: "r"(dst), "l"(src), "r"(bytes), "r"(bar) : "memory");
}
__device__ __forceinline__ void e_s2g(void* dst, uint32_t src, uint32_t bytes) {
    asm volatile(ELECT "@p cp.async.bulk.global.shared::cta.bulk_group [%0], [%1], %2;\n}" :: "l"(dst), "r"(src), "r"(bytes) : "memory");
}
__device__ __forceinline__ void e_red(unsigned* p) { asm volatile(ELECT "@p red.relaxed.gpu.global.add.u32 [%0], 1;\n}" :: "l"(p) : "memory"); }
__device__ __forceinline__ void e_red_rel(unsigned* p) { asm volatile(ELECT "@p red.release.gpu.global.add.u32 [%0], 1;\n}" :: "l"(p) : "memory"); }

constexpr uint32_t R_WQ = 0, R_WO = 65536, R_STG = 131072;
constexpr uint32_t R_KX = R_STG, R_VX = R_STG + 16384, R_PUB = R_STG + 49152;
constexpr uint32_t R_MEMT = 196608, R_QK = R_MEMT + 8192, R_VB = R_QK + 4096, R_S = R_VB + 4096, R_OB = R_S + 4096;
constexpr uint32_t R_SC = R_OB + 2048, R_L = R_SC + 32, R_MX = R_L + 64, R_XMAX = R_MX + 1024, R_RED = R_XMAX + 256;
constexpr uint32_t R_BAR = R_RED + 128, R_END = R_BAR + 128;
constexpr uint32_t MB_S = R_BAR, MB_V = R_BAR + 8, MB_KV = R_BAR + 16, MB_W = R_BAR + 48;
constexpr int B_Q = 1, B_O = 2, B_W0 = 3, B_W1 = 4, B_R = 5, B_M = 6;
constexpr float SCORE_C = 0.08838834764831845f * 1.4426950408889634f;
#define POLL_DELAY 380
#define POLL_AFTER 10
#define LEAD_MIN 96
#define LEAD_SUB 32
#define SPLIT 4
#define OFLIP ((cta >> 1) & 1)
#define SIDE_X 0
#define FAR_GAP 3
#define NPROBE 2
#define VHEAD 0
#define V1_WAIT 0
#define PF2 0
#define WQ_AT 1
#define LORD 2
#define FAR_WG 0
#define WQ_L0 8
#define WQ_L1 10
#define WO_Q0 0
#define HOIST 0
#define WO_RES 8
#define WO_E0 0
#define WO_E1 0
#define WO_Q1 0
#define WO_G0 4

#define TRACE(i)
#define SCHED_FENCE() asm volatile("pmevent 0;" ::: "memory")
__device__ __forceinline__ uint32_t tie(uint32_t v, uint32_t dep, uint32_t zero) { return v ^ (dep & zero); }
__device__ __forceinline__ uint32_t tie(uint32_t v, float dep, uint32_t zero) { return v ^ (__float_as_uint(dep) & zero); }
__device__ __forceinline__ void lds_frag(uint32_t (&r)[4], uint32_t a) {
    asm volatile("ld.shared.v4.b32 {%0,%1,%2,%3}, [%4];" : "=r"(r[0]), "=r"(r[1]), "=r"(r[2]), "=r"(r[3]) : "r"(a) : "memory");
}
__device__ __forceinline__ void sts_frag(uint32_t a, const uint32_t (&r)[4]) {
    asm volatile("st.shared.v4.b32 [%0], {%1,%2,%3,%4};" :: "r"(a), "r"(r[0]), "r"(r[1]), "r"(r[2]), "r"(r[3]) : "memory");
}

__device__ __forceinline__ uint32_t acc_off(int lg) { return (lg >> 1) * 1024 + (lg & 1) * 256; }
__device__ __forceinline__ uint32_t acc_grp(int s, int j, int n, int wi) {
    return (s >> 1) * 32768 + (s & 1) * 512 + n * 16384 + (wi >> 1) * 8192 + (wi & 1) * 2048 + (((wi >> 1) ^ j ^ (s >> 2) ^ (s >> 3) ^ (s >> 5)) & 1) * 4096;
}
__device__ __forceinline__ uint32_t acc_line(int s, int L) { return acc_grp(s, L >> 5, (L >> 4) & 1, (L >> 2) & 3) + acc_off(L & 3); }

__device__ __forceinline__ uint32_t addmul_bf2(uint32_t a, uint32_t b, uint32_t m) {
    uint32_t t, r;
    asm("mul.rn.bf16x2 %0, %1, %2;" : "=r"(t) : "r"(b), "r"(m));
    asm("fma.rn.bf16x2 %0, %1, %2, %3;" : "=r"(r) : "r"(a), "r"(m), "r"(t));
    return r;
}
__device__ __forceinline__ uint32_t absmax_bf2(uint32_t a, uint32_t b) {
    uint32_t r; asm("max.xorsign.abs.bf16x2 %0, %1, %2;" : "=r"(r) : "r"(a), "r"(b)); return r;
}
__device__ __forceinline__ uint32_t absmax8(uint4 v) {
    return __vmaxu2(__vmaxu2(v.x & 0x7fff7fffu, v.y & 0x7fff7fffu), __vmaxu2(v.z & 0x7fff7fffu, v.w & 0x7fff7fffu));
}
__device__ __forceinline__ void rec_prefetch_kv(uint32_t sb, int s, int cta) {
    const uint32_t st = s & 3;
    const size_t tile = (size_t)(s * NH + (cta >> 1)) * (SEG * DH);
    asm volatile("{\n.reg .pred p;\nelect.sync _|p, 0xffffffff;\n"
                 "@p mbarrier.arrive.expect_tx.shared::cta.b64 _, [%0], 12288;\n"
                 "@p cp.async.bulk.shared::cluster.global.mbarrier::complete_tx::bytes [%1], [%2], 4096, [%0];\n"
                 "@p cp.async.bulk.shared::cluster.global.mbarrier::complete_tx::bytes [%3], [%4], 8192, [%0];\n}"
                 :: "r"(sb + MB_KV + st * 8), "r"(sb + R_KX + st * 4096), "l"(gK + tile + (cta & 1) * 2048),
                    "r"(sb + R_VX + st * 8192), "l"(gV + tile) : "memory");
}
__device__ __forceinline__ int fresh_warp() { int t; asm volatile("mov.u32 %0, %%tid.x;" : "=r"(t)); return __shfl_sync(~0u, t >> 5, 0); }
__device__ __forceinline__ int fresh_cta() { int c; asm volatile("mov.u32 %0, %%ctaid.x;" : "=r"(c)); return c; }
__device__ __forceinline__ uint32_t fresh_lane() { uint32_t l; asm volatile("mov.u32 %0, %%laneid;" : "=r"(l)); return __shfl_sync(~0u, l, l); }
#define MMA_W(acc, w, i, b0, b1) mma(acc, w[i][0], w[i][1], w[i][2], w[i][3], b0, b1)
#define MMA_W0(acc, w, i, b0, b1) mma0(acc, w[i][0], w[i][1], w[i][2], w[i][3], b0, b1)
#define PIN8(a) asm volatile("" : "+f"(a[0]), "+f"(a[1]), "+f"(a[2]), "+f"(a[3]), "+f"(a[4]), "+f"(a[5]), "+f"(a[6]), "+f"(a[7]))

template <int KH>
__device__ __forceinline__ void rec_loop(const uint32_t sb_raw, const uint32_t (&wk)[16][4], const uint32_t (&wv)[16][4],
                                         uint32_t (&wo)[16][4], unsigned char* __restrict__ acc, const int flo, const int side_raw, const uint32_t zero) {
    unsigned* const fl = gFlags + __shfl_sync(~0u, flo, 0);
    const int side = __shfl_sync(~0u, side_raw, 0), wi = fresh_warp() & 3;
    const uint32_t sb = __shfl_sync(~0u, sb_raw, 0);
    const uint32_t l16 = fresh_lane() * 16;
    [[maybe_unused]] const bool lane0 = l16 == 0;
    const int cta = fresh_cta(), half = cta & 1;
    const uint32_t rb = mapa(sb, half ^ 1);
    const int warp = KH * 4 + wi;
    int budget = 1 << 18;
    [[maybe_unused]] int kv_next = 2;
    [[maybe_unused]] uint32_t kv_mask = 0;
    uint32_t ub[4];
#pragma unroll
    for (int r = 0; r < 4; r++) { ub[r] = sb + (wi ^ r) * 512; asm volatile("" : "+r"(ub[r])); }
    const uint32_t sw = ub[0] + KH * 2048;
    constexpr int WO_E = WO_RES + (KH ? WO_E1 : WO_E0);
#define LD_B(i) ldsm4t(bf[i], ub[(i) >> 1] + l16 + (R_MEMT + KH * 2048 + ((i) & 1) * 4096))
#define LD_WO(lo, hi) _Pragma("unroll") for (int i = (lo); i < (hi); i++) lds_frag(wo[i], sw + l16 + R_WO + i * 4096)
#define LD_WQ(lo, hi) _Pragma("unroll") for (int i = (lo); i < (hi); i++) lds_frag(wq[i], sw + l16 + R_WQ + i * 4096)
#define PAIR(x0, x1, w, i) do { MMA_W(x0, w, 2 * (i), bf[i][0], bf[i][1]); MMA_W(x1, w, 2 * (i) + 1, bf[i][2], bf[i][3]); } while (0)
#define PAIR0(x0, x1, w, i) do { MMA_W0(x0, w, 2 * (i), bf[i][0], bf[i][1]); MMA_W0(x1, w, 2 * (i) + 1, bf[i][2], bf[i][3]); } while (0)
#define QK(i) do { PAIR(q0, q1, wq, i); PAIR(k0, k1, wk, i); } while (0)
#define V_HEAD() do { PAIR0(v0, v1, wv, 7); PAIR0(v2, v3, wv, 6); if (VHEAD > 4) { PAIR(v0, v1, wv, 5); PAIR(v2, v3, wv, 4); } } while (0)
#define V_TAIL() do { \
        if (VHEAD <= 4) { PAIR(v0, v1, wv, 5); PAIR(v2, v3, wv, 4); } \
        PAIR(v0, v1, wv, 3); PAIR(v2, v3, wv, 2); PAIR(v0, v1, wv, 1); PAIR(v2, v3, wv, 0); \
        const uint32_t u0 = pack_bf((v0[0] + v1[0]) + (v2[0] + v3[0]), (v0[1] + v1[1]) + (v2[1] + v3[1])); \
        const uint32_t u1 = pack_bf((v0[2] + v1[2]) + (v2[2] + v3[2]), (v0[3] + v1[3]) + (v2[3] + v3[3])); \
        const uint32_t vbo = R_VB + half * 2048 + warp * 256 + (lc >> 1); \
        st_async2(rb + vbo, u0, u1, rb + MB_V); \
        sts64(sb + vbo, u0, u1); \
        __syncwarp(); \
        e_expect(sb + MB_V, 256); } while (0)
#define PUBLISH(st, dst) do { \
        const uint32_t dn2 = __byte_perm(0x7f000000u - __float_as_uint(lds32f(sb + R_SC + par * 16 + 12)), 0, 0x3232); \
        const uint32_t po = sb + R_PUB + wi * 512 + (lc & 0x70) * 8 + (((lc >> 3) ^ lc) & 0x70); \
        _Pragma("unroll") for (int t = 0; t < 4; t++) { f[t][0] = addmul_bf2(f[t][0], f[t][2], dn2); f[t][1] = addmul_bf2(f[t][1], f[t][3], dn2); } \
        st(po, f[0][0], f[0][1], f[1][0], f[1][1]); st(po ^ 64, f[2][0], f[2][1], f[3][0], f[3][1]); \
        asm volatile("fence.proxy.async.shared::cta;" ::: "memory"); \
        __syncwarp(); \
        e_s2g(dst + (size_t)(s * NH * 2 + cta) * (NMEM * 64), sb + R_PUB + wi * 512, 1024); \
        asm volatile("cp.async.bulk.commit_group;" ::: "memory"); } while (0)
#define PUBLISH_K() do { \
        uint32_t f[4][4]; \
        _Pragma("unroll") for (int t = 0; t < 4; t++) ldsm4t(f[t], sb + R_QK + (lc & 0x100) * 8 + (lc & 0xf0) + t * 512 + 256); \
        PUBLISH(stsm4, gKm); } while (0)
#define PUBLISH_V() do { \
        uint32_t f[4][4]; \
        _Pragma("unroll") for (int t = 0; t < 4; t++) { \
            const uint2 a = lds64(sb + (lc >> 1) + R_VB + half * 2048 + t * 256), b = lds64(sb + (lc >> 1) + R_VB + half * 2048 + t * 256 + 1024); \
            f[t][0] = a.x; f[t][1] = a.y; f[t][2] = b.x; f[t][3] = b.y; } \
        PUBLISH(stsm4t, gVm); } while (0)
#define COUNT(x)

    uint32_t wq[16][4];
    LD_WQ(KH ? WQ_L1 : WQ_L0, 16);
    const uintptr_t ahi = reinterpret_cast<uintptr_t>(acc) & ~(uintptr_t)0xffffffffu;
    uint32_t p16 = (uint32_t)reinterpret_cast<uintptr_t>(acc) + acc_grp(0, KH ^ side, 0, wi) + (acc_off(l16 >> 7) + (l16 & 0x70));
    uint32_t p4 = (uint32_t)reinterpret_cast<uintptr_t>(acc) + acc_grp(0, KH ^ side, 0, wi) + (acc_off(l16 >> 7) + 128 + ((l16 & 0x70) >> 2));
#define APTR(p) reinterpret_cast<unsigned char*>(ahi | (p))
#define STAGE(m, e, o) stsm4(sw + l16 + R_MEMT + (o), h2_to_bf2(m.x), h2_to_bf2(m.y), h2_to_bf2(m.z), h2_to_bf2(__byte_perm(m.w, e, 0x5410)))
#pragma unroll 1
    for (int s = 0;; s++) {
        const uint32_t par = s & 1;
        uint32_t bf[8][4];
        [[maybe_unused]] uint32_t kx[2][4];
        uint32_t lc;
        {
            float q0[4], q1[4], k0[4], k1[4];
            {
                bool bad;
#pragma unroll 1
                do {
                    uint32_t fx = 0;
                    if (KH == FAR_WG) {
                        MMA_W0(k0, wk, 0, (uint32_t)budget, (uint32_t)budget);
#pragma unroll
                        for (int i = 1; i < FAR_GAP; i++) MMA_W(k0, wk, 0, (uint32_t)budget, (uint32_t)budget);
                        fx = __float_as_uint(k0[0]) & zero;
                    }
                    const uint4 m0 = ld_rlx4(APTR(p16 ^ fx)), m1 = ld_rlx4(APTR(p16 ^ fx) + 16384);
                    const uint32_t e0 = ld_rlx1(APTR(p4 ^ fx)), e1 = ld_rlx1(APTR(p4 ^ fx) + 16384);
                    SCHED_FENCE();
                    if (KH == 0 && wi == 3) mbar_wait(sb + MB_KV + (s & 3) * 8, (s >> 2) & 1);
                    LD_WQ(0, KH ? WQ_L1 : WQ_L0);
                    budget--;
                    COUNT(nretry);
                    SCHED_FENCE();
                    bad = ((((m0.w ^ 0x50000000u) | (m1.w ^ 0x50000000u)) | ((e0 ^ 0x50000000u) | (e1 ^ 0x50000000u))) >> 16) != 0 && budget > 0;
                    STAGE(m0, e0, 0);
                    STAGE(m1, e1, 4096);
                } while (__any_sync(~0u, bad));
            }
            __syncwarp();
            LD_B(0); LD_B(1);
            bar_sync(B_M + KH, 128);
            LD_B(2); LD_B(3); LD_B(4); LD_B(5); LD_B(6); LD_B(7);
            PAIR0(q0, q1, wq, 0); PAIR0(k0, k1, wk, 0);
            QK(1); QK(2); QK(3);
            lc = (HOIST >> KH) & 1 ? l16 : tie(l16, q0[0], zero);
            QK(4);
#pragma unroll
            for (int i = WO_RES; i < WO_E; i++) { lds_frag(wo[i], sw + lc + R_WO + i * 4096); wq[15][i & 3] = tie(wq[15][i & 3], wo[i][0], zero); }
            sts32(sb + R_MX + warp * 128 + (lc >> 2), absmax_bf2(absmax_bf2(absmax_bf2(bf[0][0], bf[0][1]), absmax_bf2(bf[0][2], bf[0][3])),
                                                                 absmax_bf2(absmax_bf2(bf[1][0], bf[1][1]), absmax_bf2(bf[1][2], bf[1][3]))));
            QK(5); QK(6); QK(7);
            stsm4(sw + l16 + R_QK, pack_bf(q0[0] + q1[0], q0[1] + q1[1]), pack_bf(q0[2] + q1[2], q0[3] + q1[3]),
                  pack_bf(k0[0] + k1[0], k0[1] + k1[1]), pack_bf(k0[2] + k1[2], k0[3] + k1[3]));
        }
        float v0[4], v1[4], v2[4], v3[4];
        [[maybe_unused]] uint2 ts = make_uint2(0, 0);
        [[maybe_unused]] const uint32_t kb = sb + R_QK + (lc & 0x100) * 8 + (lc & 0xf0) + wi * 512 + 256;
        if (KH == 0) {
            {
                const uint32_t ka = (lc & 0x70) * 8 + (((lc >> 3) ^ lc ^ (32 * wi)) & 0x70);
                ldsm4(kx[0], sb + R_KX + (s & 3) * 4096 + wi * 1024 + ka);
                ldsm4(kx[1], sb + R_KX + (s & 3) * 4096 + wi * 1024 + (ka ^ 64));
            }
            LD_WO(WO_E, WO_E + WO_Q0);
            bar_sync(B_Q, 256);
            uint32_t vx = ((lc & 0x100) * 4 + (lc & 0x70) * 8) + (((64 * (wi & 1) + ((lc >> 3) & 0x10)) ^ lc) & 0x70);
            {
                const uint32_t qa = R_QK + (lc & 0x80) * 16 + ((lc & 0x100) >> 1) + (lc & 0x70);
                uint32_t qf[4][4], kf[4];
                ldsm4t(qf[0], ub[0] + qa); ldsm4t(kf, kb);
                ldsm4t(qf[1], ub[1] + qa); ldsm4t(qf[2], ub[2] + qa); ldsm4t(qf[3], ub[3] + qa);
                float a0[4], a1[4], a2[4];
                if (VHEAD) V_HEAD();
                MMA_W0(a0, qf, 0, kx[0][0], kx[0][1]);
                MMA_W0(a2, qf, 0, kf[0], kf[1]);
                MMA_W0(a1, qf, 1, kx[0][2], kx[0][3]);
                MMA_W(a2, qf, 0, kf[2], kf[3]);
                MMA_W(a0, qf, 2, kx[1][0], kx[1][1]);
                MMA_W(a1, qf, 3, kx[1][2], kx[1][3]);
                const float u0 = (a0[0] + a0[2]) + (a1[0] + a1[2]), u1 = (a0[1] + a0[3]) + (a1[1] + a1[3]);
                asm volatile("" : "+r"(vx));
                st_async4(rb + wi * 512 + l16 + (R_S + 2048), u0, u1, a2[0] + a2[2], a2[1] + a2[3], rb + MB_S);
                sts128(sw + l16 + R_S, u0, u1, a2[0] + a2[2], a2[1] + a2[3]);
            }
            SCHED_FENCE();
            uint32_t va[4][4];
            const uint32_t vs = sb + R_VX + (s & 3) * 8192 + (wi >> 1) * 4096;
            ldsm4t(va[0], vs + vx); ldsm4t(va[1], vs + (vx ^ 32)); ldsm4t(va[2], vs + vx + 2048); ldsm4t(va[3], vs + (vx ^ 32) + 2048);
            const float4 sc = lds128f(sb + R_SC + par * 16);
            LD_WO(WO_E + WO_Q0, 16 - WO_G0);
            uint32_t ll = sb + R_L + ((lc >> 4) & 0x1c);
            asm volatile("" : "+r"(ll));
            if (!VHEAD) V_HEAD();
            V_TAIL();
            bar_arrive(B_W1, 256);
            bar_sync(B_W0, 128);
            bool bad;
#pragma unroll 1
            do {
                float sx[8], s0, s1;
                const float4 a0 = lds128f(sb + l16 + R_S), a1 = lds128f(sb + l16 + R_S + 512), a2 = lds128f(sb + l16 + R_S + 1024), a3 = lds128f(sb + l16 + R_S + 1536);
                const uint32_t ls = mbar_gate(sb + MB_S, par, l16);
                const float4 b0 = lds128f(sb + ls + R_S + 2048), b1 = lds128f(sb + ls + R_S + 2560), b2 = lds128f(sb + ls + R_S + 3072), b3 = lds128f(sb + ls + R_S + 3584);
                sx[0] = a0.x + b0.x; sx[1] = a0.y + b0.y; sx[2] = a1.x + b1.x; sx[3] = a1.y + b1.y;
                sx[4] = a2.x + b2.x; sx[5] = a2.y + b2.y; sx[6] = a3.x + b3.x; sx[7] = a3.y + b3.y;
                s0 = ((((a0.z + b0.z) + (a1.z + b1.z)) + (a2.z + b2.z)) + (a3.z + b3.z)) * sc.y;
                s1 = ((((a0.w + b0.w) + (a1.w + b1.w)) + (a2.w + b2.w)) + (a3.w + b3.w)) * sc.y;
                float m = fmaxf(fmaxf(fmaxf(fmaxf(sx[0], sx[1]), fmaxf(sx[2], sx[3])), fmaxf(sx[4], sx[5])), fmaxf(sx[6], sx[7])) * sc.x;
                m = fmaxf(fmaxf(s0, s1), m);
                const float t1 = __shfl_xor_sync(~0u, m, 1), t2 = __shfl_xor_sync(~0u, m, 2), t3 = __shfl_xor_sync(~0u, m, 3);
                const uint32_t lv = mbar_gate(sb + MB_V, par, tie(ls, m, zero));
                const uint32_t vb = sb + (lv >> 1) + R_VB + (wi >> 1) * 2048 + (wi & 1) * 512;
                const uint2 n0 = lds64(vb), n1 = lds64(vb + 1024), n2 = lds64(vb + 256), n3 = lds64(vb + 1280);
                budget -= 64;
                bad = (ls != l16 || lv != l16) && budget > 0;
                m = fmaxf(fmaxf(m, t1), fmaxf(t2, t3));
#pragma unroll
                for (int i = 0; i < 4; i++) sx[i] = ex2(fmaf(sx[i], sc.x, -m));
                s0 = ex2((s0 - sc.z) - m); s1 = ex2((s1 - sc.z) - m);
#pragma unroll
                for (int i = 4; i < 8; i++) sx[i] = ex2(fmaf(sx[i], sc.x, -m));
                const uint32_t p0 = pack_bf(sx[0], sx[1]), p1 = pack_bf(sx[2], sx[3]), p2 = pack_bf(sx[4], sx[5]), p3 = pack_bf(sx[6], sx[7]);
                const uint32_t pv = pack_bf(s0, s1);
                MMA_W0(v0, va, 0, p0, p1);
                MMA_W0(v1, va, 1, p0, p1);
                mma(v0, n0.x, n0.y, n1.x, n1.y, pv, pv);
                mma(v1, n2.x, n2.y, n3.x, n3.y, pv, pv);
                MMA_W(v0, va, 2, p2, p3);
                MMA_W(v1, va, 3, p2, p3);
                const float l = (fmaf(s0 + s1, sc.w, (sx[0] + sx[1]) + (sx[2] + sx[3])) + (sx[4] + sx[5])) + (sx[6] + sx[7]);
                const float l1 = __shfl_xor_sync(~0u, l, 1), l2 = __shfl_xor_sync(~0u, l, 2), l3 = __shfl_xor_sync(~0u, l, 3);
                stsm4(sw + l16 + R_OB, pack_bf(v0[0], v0[1]), pack_bf(v0[2], v0[3]), pack_bf(v1[0], v1[1]), pack_bf(v1[2], v1[3]));
                sts32(ll, __float_as_uint((l + l1) + (l2 + l3)));
                COUNT(nredo);
            } while (__any_sync(~0u, bad));
        } else {
            LD_WO(WO_E, WO_E + WO_Q1);
            bar_sync(B_Q, 256);
            SCHED_FENCE();
            if (KH == 1)
                asm volatile("{ .reg .pred p; .reg .u32 t; setp.eq.u32 p, %1, 0; mov.u32 t, %%globaltimer_lo; or.b32 t, t, 1; @p st.relaxed.gpu.global.u32 [%0], t; }"
                             :: "l"(wi ? fl + F_PH : gTime + s * NREC + cta), "r"(l16 + (wi == 0 || (wi == 2 && cta == 0) ? 0 : 1)) : "memory");
            uint32_t kvf = 2;
            if (wi == 1 && kv_mask != ~0u) kvf = ld_rlx1(fl + F_KV + (cta >> 1) * NT64 + (lc >> 4));
            V_HEAD();
            V_TAIL();
            if (wi != 0) bar_arrive(B_W1, 256);
            SCHED_FENCE();
            if (wi == 1) {
                e_expect(sb + MB_S, 2048);
                kv_mask = __ballot_sync(~0u, kvf >= 2);
                const bool kv_ok = (kv_mask >> ((kv_next >> 1) & 31)) & 1;
                if (kv_next < NSEG && (kv_ok || kv_next == s + 1)) {
                    if (!kv_ok) wait_flag(fl + F_KV + (cta >> 1) * NT64 + (kv_next >> 1), 2);
#pragma unroll 1
                    do { rec_prefetch_kv(sb, kv_next, cta); kv_next++; } while ((kv_next & 1) && kv_next <= s + 3);
                }
            } else if (wi == 3) {
                    const int sp = min(s + 3, NSEG - 1);
                    asm volatile("prefetch.global.L2 [%0];" :: "l"((lc < 256 ? acc + acc_line(sp, (cta + (lc >> 5) * 2) & 63)
                                                                          : reinterpret_cast<unsigned char*>(gTime + (sp - 1) * NREC)) + (lc & 16) * 8));
                if (s == 0) {
                    uint2 t;
                    do { t = ld_rlx2(reinterpret_cast<const unsigned char*>(fl + F_W) + (lc >> 1)); } while (__any_sync(~0u, t.x == 0 || t.y == 0) && --budget > 0);
                    const uint32_t wm = __vmaxu2(t.x, t.y) & 0x7fffffffu;
                    sts32(sb + R_RED, __float_as_uint(__uint_as_float(__reduce_max_sync(~0u, wm & 0xffff0000u)) * __uint_as_float(__reduce_max_sync(~0u, wm << 16))));
                    __syncwarp();
                }
                const float dn = __uint_as_float(0x7f000000u - __float_as_uint(lds32f(sb + R_SC + par * 16 + 12)));
                const uint4 ta = lds128(sb + R_MX + lc), tb = lds128(sb + R_MX + 512 + lc);
                uint32_t mx = absmax_bf2(absmax_bf2(absmax_bf2(ta.x, ta.y), absmax_bf2(ta.z, ta.w)), absmax_bf2(absmax_bf2(tb.x, tb.y), absmax_bf2(tb.z, tb.w)));
                mx = __reduce_max_sync(~0u, max(mx & 0x7fffu, (mx >> 16) & 0x7fffu));
                const float am = fmaxf(__uint_as_float(mx << 16) * dn, lds32f(sb + R_XMAX + s * 4));
                int e = 120 - (int)(__float_as_uint(am * lds32f(sb + R_RED)) >> 23);
                e = min(max(e, -60), 60);
                const float d2 = __uint_as_float((127 - e) << 23);
                sts128(sb + R_SC + (par ^ 1) * 16, SCORE_C * d2, SCORE_C * d2 * d2, (float)e, __uint_as_float((127 + e) << 23));
            } else {
                asm volatile("cp.async.bulk.wait_group 0;" ::: "memory");
                if (s > 0) e_red(fl + F_M + (cta >> 1) * NSEG + s - 1);
                if (wi == 2) {
                    PUBLISH_K();
                } else {
                    bar_sync(B_W1, 256);
                    PUBLISH_V();
                }
                if (s == NSEG - 1) { asm volatile("cp.async.bulk.wait_group 0;" ::: "memory"); e_red(fl + F_M + (cta >> 1) * NSEG + s); }
            }
            if (wi != 0) mbar_wait(sb + MB_V, par);
            LD_WO(WO_E + WO_Q1, 16);
            SCHED_FENCE();
            if (wi == 1) ts = ld_rlx2(reinterpret_cast<const unsigned char*>(gTime + s * NREC) + (lc >> 1));
        }
        bar_sync(B_O, 256);
        {
            uint32_t ob[4][4];
#define G4(M, i) do { M(v0, wo, 4 * (i), ob[i][0], ob[i][1]); M(v1, wo, 4 * (i) + 1, ob[i][0], ob[i][1]); \
                      M(v2, wo, 4 * (i) + 2, ob[i][2], ob[i][3]); M(v3, wo, 4 * (i) + 3, ob[i][2], ob[i][3]); } while (0)
            ldsm4t(ob[0], sb + l16 + R_OB);
            ldsm4t(ob[1], sb + l16 + R_OB + 512);
            ldsm4t(ob[2], sb + l16 + R_OB + 1024);
            ldsm4t(ob[3], sb + l16 + R_OB + 1536);
            const uint32_t lo = (HOIST >> KH) & 1 ? l16 : tie(lc, ob[0][0], zero);
            const float2 l = lds64f(sb + R_L + ((lc >> 1) & 0x18));
            const float up = lds32f(sb + R_SC + (par ^ 1) * 16 + 12);
            if (KH == 0) { LD_WO(16 - WO_G0, 16); }
            G4(MMA_W0, 0);
            G4(MMA_W, 1);
            const float i0 = up * rcp(__uint_as_float(tie(__float_as_uint(l.x), v0[0], zero))), i1 = up * rcp(__uint_as_float(tie(__float_as_uint(l.y), v0[0], zero)));
            const uint32_t ap = (uint32_t)reinterpret_cast<uintptr_t>(acc) + acc_grp(s + 1, half, KH ^ OFLIP, wi);
            const uint32_t w16 = ap + (acc_off(lo >> 7) + (lo & 0x70)), w4 = ap + (acc_off(lo >> 7) + 128 + ((lo & 0x70) >> 2));
            G4(MMA_W, 2);
            wo[14][0] = tie(wo[14][0], w16 | w4, zero);
            G4(MMA_W, 3);
            if (s < NSEG - 1) red_h8(APTR(w16), pack_h((v0[0] + v2[0]) * i0, (v0[1] + v2[1]) * i1), pack_h((v0[2] + v2[2]) * i0, (v0[3] + v2[3]) * i1),
                   pack_h((v1[0] + v3[0]) * i0, (v1[1] + v3[1]) * i1), pack_h((v1[2] + v3[2]) * i0, 1.f));
            if (s < NSEG - 1) red_h2(APTR(w4), pack_h((v1[3] + v3[3]) * i1, 1.f));
            if (s == NSEG - 1) break;
            SCHED_FENCE();
            const uint32_t tr = clk32();
            uint32_t w = POLL_DELAY;
            const int po = (int)acc_grp(s + 1, KH ^ side, 0, wi) - (int)acc_grp(s + 1, half, KH ^ OFLIP, wi);
            p16 = w16 + po; p4 = w4 + po;
            if (KH == 1 && wi == 1) {
                while (__any_sync(~0u, ts.x == 0 || ts.y == 0) && --budget > 0)
                    ts = ld_rlx2(reinterpret_cast<const unsigned char*>(gTime + s * NREC) + (lc >> 1));
                const uint32_t now = gtime32();
                const uint32_t age = min(now - ts.x + 64, now - ts.y + 64);
                const int lead = __reduce_min_sync(~0u, (lc >> 4) == (cta >> 1) ? age : ~0u) - __reduce_min_sync(~0u, age);
                if (lead >= LEAD_MIN && lead < 4096) w += ((lead - LEAD_SUB) * 29) >> 4;
            }
            LD_WQ(KH ? WQ_L1 : WQ_L0, 16);
            while (clk32() - tr < w) {}
            asm volatile("" : "+r"(p16), "+r"(p4));
            SCHED_FENCE();
            bar_sync(B_R, 256);
        }
    }
}

__device__ __forceinline__ uint32_t frag_absmax(const uint32_t (&w)[16][4]) {
    uint32_t m = 0;
#pragma unroll
    for (int i = 0; i < 16; i++) m = __vmaxu2(m, absmax8(make_uint4(w[i][0], w[i][1], w[i][2], w[i][3])));
    return __reduce_max_sync(~0u, max(m & 0xffffu, m >> 16)) << 16;
}

__device__ __forceinline__ void pf_line(const bf16* p) {
    asm volatile("prefetch.global.L2 [%0];" :: "l"(p));
    if (PF2) asm volatile("prefetch.global.L2 [%0];" :: "l"(p + 32));
}
__global__ void __cluster_dims__(2, 1, 1) __launch_bounds__(256, 1)
rec_kernel(const __grid_constant__ Maps m, unsigned char* __restrict__ acc, const uint32_t zero) {
    extern __shared__ __align__(1024) unsigned char smem_raw[];
    const uint32_t sb = s2u(smem_raw);
    if (LORD == 0) asm volatile("griddepcontrol.launch_dependents;");
    TRACE(0);
    const int tid = threadIdx.x, lane = tid & 31, warp = __shfl_sync(~0u, tid >> 5, 0);
    const int cta = fresh_cta(), head = cta >> 1, half = cta & 1;
    if (tid == 0) {
        mbar_init(sb + MB_S, 1); mbar_init(sb + MB_V, 8);
#pragma unroll 1
        for (int i = 0; i < 8; i++) mbar_init(sb + MB_KV + i * 8, 1);
        asm volatile("fence.mbarrier_init.release.cluster;" ::: "memory");
    }
    __syncwarp();
    const unsigned epoch = ld_rlx1(&gEpoch);
    {
#define FLIP(p) reinterpret_cast<const unsigned char*>(reinterpret_cast<uintptr_t>(p) ^ 4096)
        const unsigned char* const pa = acc + acc_line(warp * 2 + (cta >> 5), cta & 31) + 224;
        uint32_t best[2] = {~0u, ~0u}, v = 0;
        if (lane < 2) asm volatile("atom.relaxed.gpu.global.exch.b32 %0, [%1], 0;" : "=r"(v) : "l"(lane ? FLIP(pa) : pa) : "memory");
        v = __reduce_or_sync(~0u, v) & zero;
        if (lane == 0) {
#pragma unroll 1
            for (int i = 0; i < NPROBE; i++) {
                const uint32_t t0 = clk32_after(v);
                asm volatile("atom.relaxed.gpu.global.add.u32 %0, [%1], 1;" : "=r"(v) : "l"(((i ^ warp) & 1) ? FLIP(pa) : pa) : "memory");
                const uint32_t dt = clk32_after(v) - t0;
                if ((i ^ warp) & 1) best[1] = min(best[1], dt); else best[0] = min(best[0], dt);
            }
            sts64(sb + R_RED + warp * 8, best[0], best[1]);
        }
    }
    __syncthreads();
    TRACE(1);
    auto load_w = [&](int i) {
        const uint32_t dst = sb + (i == 2 ? R_WQ : i == 1 ? R_STG : R_WO), bar = sb + MB_W + i * 8;
        const CUtensorMap* w = i == 0 ? &m.wk : i == 1 ? &m.wv : i == 2 ? &m.wq : &m.wo;
        e_expect(bar, 65536);
#pragma unroll 1
        for (int k = 0; k < 8; k++)
            e_tma2d(dst + k * 8192, w, i < 3 ? cta * 64 : half * 256 + (k >> 1) * 64, i < 3 ? k * 64 : head * DH + (k & 1) * 64, bar);
    };
    if (warp == 0) { load_w(0); load_w(1); if (WQ_AT == 2) load_w(2); }
    unsigned* const fl = gFlags + (__shfl_sync(~0u, epoch, 0) & 1) * F_END;
    int side;
    {
        const uint2 t = lds64(sb + R_RED + (lane & 7) * 8);
        side = (__reduce_min_sync(~0u, t.y) < __reduce_min_sync(~0u, t.x)) ^ SIDE_X;
    }

    const int wi = warp & 3, kh = warp >> 2;
    uint32_t wk[16][4], wv[16][4], wo[16][4];
    const uint32_t wrow = sb + (uint32_t)(256 * (kh ^ side) + (lane >> 4) * 8 + (lane & 7)) * 128 + (((2 * wi + ((lane >> 3) & 1)) ^ (lane & 7)) << 4);
#define KROW(i) ((4 * (((i) >> 1) & 1) + (wi ^ ((i) >> 2))) * 4096 + ((i) & 1) * 2048)
    mbar_wait(sb + MB_W, 0);
    TRACE(2);
#pragma unroll
    for (int i = 0; i < 16; i++) ldsm4t(wk[i], wrow + R_WO + KROW(i));
    __syncthreads();
    if (warp == 0) { if (WQ_AT == 0) load_w(2); if (WQ_AT != 1) load_w(3); }
    TRACE(8);
    mbar_wait(sb + MB_W + 8, 0);
    TRACE(9);
    if (warp == 0 && WQ_AT == 1) { load_w(2); load_w(3); }
#pragma unroll
    for (int i = 0; i < 16; i++) ldsm4t(wv[i], wrow + R_STG + KROW(i));
    const uint32_t vmax = frag_absmax(wv);
    mbar_wait(sb + MB_W + 16, 0);
    TRACE(3);
#pragma unroll
    for (int i = 0; i < 16; i++) ldsm4t(wo[i], wrow + R_WQ + KROW(i));
    __syncthreads();
#pragma unroll
    for (int i = 0; i < 16; i++) sts_frag(sb + tid * 16 + R_WQ + i * 4096, wo[i]);
    mbar_wait(sb + MB_W + 24, 0);
    TRACE(4);
    const uint32_t orow = sb + R_WO + (((kh ^ OFLIP) << 1) + (wi >> 1)) * 16384 + (uint32_t)((lane >> 4) * 8 + (lane & 7)) * 128 + (((4 * (warp & 1) + ((lane >> 3) & 1)) ^ (lane & 7)) << 4);
#pragma unroll
    for (int i = 0; i < 16; i++) ldsm4t(wo[i], (orow ^ ((i & 1) << 5)) + (i >> 1) * 2048);
    const uint32_t omax = frag_absmax(wo);
    if (lane == 0) sts32(sb + R_RED + 64 + warp * 4, vmax | (omax >> 16));
    __syncthreads();
#pragma unroll
    for (int i = WO_RES; i < 16; i++) sts_frag(sb + tid * 16 + R_WO + i * 4096, wo[i]);
    TRACE(5);
    if (warp == 6) {
        const uint32_t t = __float_as_uint(lds32f(sb + R_RED + 64 + (lane & 7) * 4));
        const uint32_t a = __reduce_max_sync(~0u, t & 0xffff0000u), b = __reduce_max_sync(~0u, t & 0xffffu);
        if (lane == 0) st_rlx1(fl + F_W + cta, a | b | 0x80000000u);
    } else if (warp == 7) {
        wait_flag(fl + F_BAR, NREC);
        const uint2 t = ld_rlx2(fl + F_X + lane * 2);
        const int e = (int)ld_rlx1(fl + F_BAR + 1);
        sts64(sb + R_XMAX + lane * 8, t.x, t.y);
        const float dn = __uint_as_float((127 - e) << 23);
        sts128(sb + R_SC, SCORE_C * dn, SCORE_C * dn * dn, (float)e, __uint_as_float((127 + e) << 23));
    } else if (warp == 1) {
        wait_flag(fl + F_KV + head * NT64, 2);
        rec_prefetch_kv(sb, 0, cta); rec_prefetch_kv(sb, 1, cta);
    }
    __syncwarp();
    asm volatile("barrier.cluster.arrive.relaxed.aligned; barrier.cluster.wait.aligned;" ::: "memory");
    __syncthreads();
    TRACE(6);
    if (fresh_warp() < 4) rec_loop<0>(sb, wk, wv, wo, acc, (int)(fl - gFlags), side, zero);
    else rec_loop<1>(sb, wk, wv, wo, acc, (int)(fl - gFlags), side, zero);
    cluster_sync();
    TRACE(7);
    if (LORD == 1) asm volatile("griddepcontrol.wait;" ::: "memory");
}

__device__ __forceinline__ void wg_ss128(float (&d)[64], uint64_t ad, uint64_t bd, uint32_t acc) {
    asm volatile("{\n.reg .pred p;\nsetp.ne.u32 p, %66, 0;\n"
                 "wgmma.mma_async.sync.aligned.m64n128k16.f32.bf16.bf16 {%0,%1,%2,%3,%4,%5,%6,%7,%8,%9,%10,%11,%12,%13,%14,%15,%16,%17,%18,%19,%20,%21,%22,%23,%24,%25,%26,%27,%28,%29,%30,%31,%32,%33,%34,%35,%36,%37,%38,%39,%40,%41,%42,%43,%44,%45,%46,%47,%48,%49,%50,%51,%52,%53,%54,%55,%56,%57,%58,%59,%60,%61,%62,%63}, %64, %65, p, 1, 1, 0, 1;\n}"
                 : "+f"(d[0]), "+f"(d[1]), "+f"(d[2]), "+f"(d[3]), "+f"(d[4]), "+f"(d[5]), "+f"(d[6]), "+f"(d[7]), "+f"(d[8]), "+f"(d[9]), "+f"(d[10]), "+f"(d[11]), "+f"(d[12]), "+f"(d[13]), "+f"(d[14]), "+f"(d[15]), "+f"(d[16]), "+f"(d[17]), "+f"(d[18]), "+f"(d[19]), "+f"(d[20]), "+f"(d[21]), "+f"(d[22]), "+f"(d[23]), "+f"(d[24]), "+f"(d[25]), "+f"(d[26]), "+f"(d[27]), "+f"(d[28]), "+f"(d[29]), "+f"(d[30]), "+f"(d[31]), "+f"(d[32]), "+f"(d[33]), "+f"(d[34]), "+f"(d[35]), "+f"(d[36]), "+f"(d[37]), "+f"(d[38]), "+f"(d[39]), "+f"(d[40]), "+f"(d[41]), "+f"(d[42]), "+f"(d[43]), "+f"(d[44]), "+f"(d[45]), "+f"(d[46]), "+f"(d[47]), "+f"(d[48]), "+f"(d[49]), "+f"(d[50]), "+f"(d[51]), "+f"(d[52]), "+f"(d[53]), "+f"(d[54]), "+f"(d[55]), "+f"(d[56]), "+f"(d[57]), "+f"(d[58]), "+f"(d[59]), "+f"(d[60]), "+f"(d[61]), "+f"(d[62]), "+f"(d[63])
                 : "l"(ad), "l"(bd), "r"(acc));
}
__device__ __forceinline__ void wg_ss64tt(float (&d)[32], uint64_t ad, uint64_t bd, uint32_t acc) {
    asm volatile("{\n.reg .pred p;\nsetp.ne.u32 p, %34, 0;\n"
                 "wgmma.mma_async.sync.aligned.m64n64k16.f32.bf16.bf16 {%0,%1,%2,%3,%4,%5,%6,%7,%8,%9,%10,%11,%12,%13,%14,%15,%16,%17,%18,%19,%20,%21,%22,%23,%24,%25,%26,%27,%28,%29,%30,%31}, %32, %33, p, 1, 1, 1, 1;\n}"
                 : "+f"(d[0]), "+f"(d[1]), "+f"(d[2]), "+f"(d[3]), "+f"(d[4]), "+f"(d[5]), "+f"(d[6]), "+f"(d[7]), "+f"(d[8]), "+f"(d[9]), "+f"(d[10]), "+f"(d[11]), "+f"(d[12]), "+f"(d[13]), "+f"(d[14]), "+f"(d[15]), "+f"(d[16]), "+f"(d[17]), "+f"(d[18]), "+f"(d[19]), "+f"(d[20]), "+f"(d[21]), "+f"(d[22]), "+f"(d[23]), "+f"(d[24]), "+f"(d[25]), "+f"(d[26]), "+f"(d[27]), "+f"(d[28]), "+f"(d[29]), "+f"(d[30]), "+f"(d[31])
                 : "l"(ad), "l"(bd), "r"(acc));
}
__device__ __forceinline__ void wg_rs80(float (&d)[40], uint32_t a0, uint32_t a1, uint32_t a2, uint32_t a3, uint64_t bd, uint32_t acc) {
    asm volatile("{\n.reg .pred p;\nsetp.ne.u32 p, %45, 0;\n"
                 "wgmma.mma_async.sync.aligned.m64n80k16.f32.bf16.bf16 {%0,%1,%2,%3,%4,%5,%6,%7,%8,%9,%10,%11,%12,%13,%14,%15,%16,%17,%18,%19,%20,%21,%22,%23,%24,%25,%26,%27,%28,%29,%30,%31,%32,%33,%34,%35,%36,%37,%38,%39}, {%40,%41,%42,%43}, %44, p, 1, 1, 0;\n}"
                 : "+f"(d[0]), "+f"(d[1]), "+f"(d[2]), "+f"(d[3]), "+f"(d[4]), "+f"(d[5]), "+f"(d[6]), "+f"(d[7]), "+f"(d[8]), "+f"(d[9]), "+f"(d[10]), "+f"(d[11]), "+f"(d[12]), "+f"(d[13]), "+f"(d[14]), "+f"(d[15]), "+f"(d[16]), "+f"(d[17]), "+f"(d[18]), "+f"(d[19]), "+f"(d[20]), "+f"(d[21]), "+f"(d[22]), "+f"(d[23]), "+f"(d[24]), "+f"(d[25]), "+f"(d[26]), "+f"(d[27]), "+f"(d[28]), "+f"(d[29]), "+f"(d[30]), "+f"(d[31]), "+f"(d[32]), "+f"(d[33]), "+f"(d[34]), "+f"(d[35]), "+f"(d[36]), "+f"(d[37]), "+f"(d[38]), "+f"(d[39])
                 : "r"(a0), "r"(a1), "r"(a2), "r"(a3), "l"(bd), "r"(acc));
}
__device__ __forceinline__ void wg_rs64t(float (&d)[32], uint32_t a0, uint32_t a1, uint32_t a2, uint32_t a3, uint64_t bd, uint32_t acc) {
    asm volatile("{\n.reg .pred p;\nsetp.ne.u32 p, %37, 0;\n"
                 "wgmma.mma_async.sync.aligned.m64n64k16.f32.bf16.bf16 {%0,%1,%2,%3,%4,%5,%6,%7,%8,%9,%10,%11,%12,%13,%14,%15,%16,%17,%18,%19,%20,%21,%22,%23,%24,%25,%26,%27,%28,%29,%30,%31}, {%32,%33,%34,%35}, %36, p, 1, 1, 1;\n}"
                 : "+f"(d[0]), "+f"(d[1]), "+f"(d[2]), "+f"(d[3]), "+f"(d[4]), "+f"(d[5]), "+f"(d[6]), "+f"(d[7]), "+f"(d[8]), "+f"(d[9]), "+f"(d[10]), "+f"(d[11]), "+f"(d[12]), "+f"(d[13]), "+f"(d[14]), "+f"(d[15]), "+f"(d[16]), "+f"(d[17]), "+f"(d[18]), "+f"(d[19]), "+f"(d[20]), "+f"(d[21]), "+f"(d[22]), "+f"(d[23]), "+f"(d[24]), "+f"(d[25]), "+f"(d[26]), "+f"(d[27]), "+f"(d[28]), "+f"(d[29]), "+f"(d[30]), "+f"(d[31])
                 : "r"(a0), "r"(a1), "r"(a2), "r"(a3), "l"(bd), "r"(acc));
}
__device__ __forceinline__ void wg_fence() { asm volatile("wgmma.fence.sync.aligned;" ::: "memory"); }
__device__ __forceinline__ void wg_commit() { asm volatile("wgmma.commit_group.sync.aligned;" ::: "memory"); }
template <int N> __device__ __forceinline__ void wg_wait() { asm volatile("wgmma.wait_group.sync.aligned %0;" :: "n"(N) : "memory"); }
template <int N> __device__ __forceinline__ void pin(float (&d)[N]) {
#pragma unroll
    for (int i = 0; i < N; i++) asm volatile("" : "+f"(d[i]) :: "memory");
}
__device__ __forceinline__ uint64_t mk_desc(uint32_t addr, uint32_t lbo) {
    return (uint64_t)((addr & 0x3FFFF) >> 4) | ((uint64_t)(lbo >> 4) << 16) | ((uint64_t)64 << 32) | ((uint64_t)1 << 62);
}
__device__ __forceinline__ float phi(float t) { return (t > 0.f ? t + 1.f : ex2(t * 1.4426950408889634f)) + 1e-6f; }

constexpr uint32_t U_W = 0, U_RING = 131072, U_STAGE = 10240, U_STG = U_RING + 8 * U_STAGE, U_BAR = U_STG + 16384, U_Z = U_BAR + 384, U_END = U_Z + 512;
constexpr uint32_t UB_FULL = 0, UB_EMPTY = 32, UB_STAGED = 64, UB_FREE = 72, UB_WG = 96, UB_W = 192, UB_WFREE = 256;
enum { J_KV, J_QA, J_BKV, J_BQ, J_F, J_END };
#define PP_K 4
#define DEFER 1
#define PP_MASK 0x1d
#define QA_GATE 0
#define EPOCH_J 32
#define PF_T 16
#define WIN_A 100
#define WIN_B 1300
__device__ __forceinline__ void quiet_window(const unsigned* fl) {
    const uint32_t ph = __shfl_sync(~0u, ld_rlx1(fl + F_PH), 0);
    if (gtime32() - ph >= WIN_A) while (gtime32() - ph < WIN_B) {}
}

struct Job { int t0, t1, p0, p1; };
__device__ __forceinline__ int first_job(int j) { return j >= 64 ? J_BKV : J_KV; }
__device__ __forceinline__ int next_job(int J, int j) {
    return J == J_KV ? (j < 32 ? J_QA : J_BKV) : J == J_BKV ? (j >= 64 ? J_F : J_BQ) : J == J_BQ ? J_F : J_END;
}
__device__ __forceinline__ Job job_of(int J, int j) {
    const int i = j & 31, tb0 = j >= 64 ? 0 : (i >> 2) * 4, tb1 = j >= 64 ? NT64 : tb0 + 4;
    if (J == J_KV || J == J_QA) return {0, NT64, i, j >> 5};
    if (J == J_BKV) return {tb0, tb1, (j >= 64 ? i : 4 + (i & 3)) * 16 + (tb0 >> 1), 0};
    if (J == J_BQ) return {tb0, tb1, i & 3, 0};
    return {0, NT64, i & 3, j >= 64 ? 8 : i >> 2};
}
__device__ __forceinline__ const CUtensorMap* job_w(const Maps& m, int J, int j, int& c0, int& d1, int& r0, const bf16*& raw, int& ld) {
    const int i = j & 31;
    c0 = (i & 3) * 128; d1 = 64; r0 = 0; ld = HD;
    if (J == J_KV) { c0 = i * 128; raw = j < 32 ? m.pk : m.pv; return j < 32 ? &m.wk : &m.wv; }
    if (J == J_QA) { c0 = i * 128; raw = m.pq; return &m.wq; }
    ld = 3 * DM; raw = m.pb;
    if (J == J_BKV) { c0 = 512 + (j >= 64 ? i : 4 + (i & 3)) * 64; d1 = 512; return &m.wb; }
    if (J == J_BQ) return &m.wb;
    ld = DM;
    if (j >= 64) { raw = m.po2; return &m.wo2; }
    r0 = (i >> 2) * 512; raw = m.po;
    return &m.wo;
}
__device__ __forceinline__ void stage_half(uint32_t base, int lane, const uint32_t* pk) {
    const uint32_t a = base + (((lane >> 3) & 1) * 8 + (lane & 7)) * 128 + (((lane >> 4) ^ (lane & 7)) << 4);
#pragma unroll
    for (int i = 0; i < 4; i++) stsm4(a ^ (i << 5), pk[4 * i], pk[4 * i + 1], pk[4 * i + 2], pk[4 * i + 3]);
}
__device__ __forceinline__ void reduce_rows(bf16* __restrict__ out, int lane, int t, int cg, int row0) {
    const int row = row0 + (lane >> 4), c16 = lane & 15;
    const unsigned char* p = reinterpret_cast<const unsigned char*>(gP) + (size_t)(t * 4 + cg) * 16384 + (c16 >> 3) * 8192 + row * 128 + (((c16 ^ row) & 7) << 4);
    uint4 v[9];
#pragma unroll
    for (int k = 0; k < 9; k++) v[k] = ld_rlx4(p + (size_t)k * (NT64 * 4 * 16384));
    float f[8] = {};
#pragma unroll
    for (int k = 0; k < 9; k++) {
        f[0] += bf_lo(v[k].x); f[1] += bf_hi(v[k].x); f[2] += bf_lo(v[k].y); f[3] += bf_hi(v[k].y);
        f[4] += bf_lo(v[k].z); f[5] += bf_hi(v[k].z); f[6] += bf_lo(v[k].w); f[7] += bf_hi(v[k].w);
    }
    *reinterpret_cast<uint4*>(out + (size_t)(t * 64 + row) * DM + cg * 128 + c16 * 8) =
        make_uint4(pack_bf(f[0], f[1]), pack_bf(f[2], f[3]), pack_bf(f[4], f[5]), pack_bf(f[6], f[7]));
}

__device__ __forceinline__ void bulk_consumer(const uint32_t sb, unsigned* const fl, bf16* __restrict__ out, const int j) {
    const int tid = threadIdx.x, lane = tid & 31, warp = fresh_warp(), wg = warp >> 2, w4 = warp & 3, cg = j & 3;
    const uint32_t ring = sb + U_RING + wg * 4 * U_STAGE, bars = sb + U_BAR + wg * UB_WG, full = bars + UB_FULL, empty = bars + UB_EMPTY;
    uint32_t round = 0, nout = 0, njob = 0;
#pragma unroll 1
    for (int J = first_job(j); J != J_END; J = next_job(J, j), njob++) {
        const Job job = job_of(J, j);
        const int t0 = job.t0, t1 = job.t1, p0 = job.p0;
        const uint32_t stg0 = sb + U_STG + warp * 2048, stg1 = J == J_QA ? sb + U_STG + (warp ^ 4) * 2048 : ring + w4 * U_STAGE + 8192;
        const bool build = J == J_F && j >= 64;
        if (J == J_QA || J == J_BQ) wait_flag(fl + F_BAR, NREC);
        if (J == J_QA) { mbar_wait(bars + UB_FREE, (nout & 1) ^ 1); bar_arrive(6 + wg, 256); }
        if (J == J_BQ || build) wait_flag(fl + F_B, 72);
        if (J == J_BQ) {
        {
            const int col = tid >> 1, zt = cg * 2 + (col >> 6), n = zt < 4 ? 4 : 32;
            float z = 0.f;
#pragma unroll
            for (int k = 0; k < 32; k++) if (k < n) z += __ldcg(gZp + zt * 4096 + (2 * k + (tid & 1)) * 64 + (col & 63));
            z += __shfl_xor_sync(~0u, z, 1);
            sts32(sb + U_Z + col * 4, __float_as_uint(z));
        }
            bar_sync(7, 256);
        }
        if (build) {
#pragma unroll 1
            for (int k = 0; k < 8; k++) mbar_wait(sb + U_BAR + UB_W + k * 8, njob & 1);
#pragma unroll 1
        for (int hl = 0; hl < 4; hl++) {
            const int hd = hl * 8 + warp, n = hl < 2 ? 2 : 16;
            const float* src = gKVp + (hd >> 2) * 16384 + (hd & 3) * 256 + (lane >> 2) * 16 + (lane & 3) * 2;
            float2 s0 = {0.f, 0.f}, s1 = s0, s2 = s0, s3 = s0;
#pragma unroll
            for (int k = 0; k < 16; k++) if (k < n) {
                const float2 a = __ldcg(reinterpret_cast<const float2*>(src + k * 1024)), b = __ldcg(reinterpret_cast<const float2*>(src + k * 1024 + 128));
                const float2 d = __ldcg(reinterpret_cast<const float2*>(src + k * 1024 + 8)), e = __ldcg(reinterpret_cast<const float2*>(src + k * 1024 + 136));
                s0.x += a.x; s0.y += a.y; s1.x += b.x; s1.y += b.y; s2.x += d.x; s2.y += d.y; s3.x += e.x; s3.y += e.y;
            }
            const uint32_t a0 = pack_bf(s0.x, s0.y), a1 = pack_bf(s1.x, s1.y), a2 = pack_bf(s2.x, s2.y), a3 = pack_bf(s3.x, s3.y);
            const uint32_t base = sb + U_W + (hd * 16 + ((lane >> 3) & 1) * 8 + (lane & 7)) * 128 + (((lane >> 4) ^ (lane & 7)) << 4);
#pragma unroll
            for (int q = 0; q < 8; q++) {
                const uint32_t ad = (base ^ ((q & 3) << 5)) + (q >> 2) * 65536;
                uint32_t b[4];
                float d0[4], d1[4];
                ldsm4t(b, ad);
                mma0(d0, a0, a1, a2, a3, b[0], b[1]);
                mma0(d1, a0, a1, a2, a3, b[2], b[3]);
                stsm4(ad, pack_bf(d0[0], d0[1]), pack_bf(d0[2], d0[3]), pack_bf(d1[0], d1[1]), pack_bf(d1[2], d1[3]));
            }
        }
            asm volatile("fence.proxy.async.shared::cta;" ::: "memory");
            bar_sync(7, 256);
        }
        const bool pp = (PP_MASK >> J) & 1;
        bool held = false;
        int red_next = J == J_F && j < 64 ? wg : NT64;
        float kv[32], zs[16];
#pragma unroll
        for (int i = 0; i < 32; i++) kv[i] = 0.f;
#pragma unroll
        for (int i = 0; i < 16; i++) zs[i] = 0.f;
#pragma unroll 1
        for (int t = t0 + wg; t < t1; t += 2) {
        if (t == t0 + wg) TRACE(1 + J * 4);
        if (t == t0 + wg + 2) TRACE(2 + J * 4);
        if (t + 2 >= t1) TRACE(3 + J * 4);
        if (J == J_QA && t == 10 + wg) TRACE(21);
        if (t != t0 && (pp || t == t0 + 1)) bar_sync(10 + wg, 256);
        float acc[64];
        uint32_t fr;
#pragma unroll
        for (int k = 0; k < 8; k++) {
            if (t < t0 + 2) mbar_wait(sb + U_BAR + UB_W + k * 8, njob & 1);
            mbar_wait(full + (k & 3) * 8, (round + (k >> 2)) & 1);
            wg_fence();
            const uint64_t ad = mk_desc(ring + (k & 3) * U_STAGE, 16), bd = mk_desc(sb + U_W + k * 8192, 65536);
#pragma unroll
            for (int q = 0; q < 4; q++) wg_ss128(acc, ad + q * 2, bd + q * 128, k + q);
            wg_commit();
            if (k == 0 && held) {
                asm volatile("fence.proxy.async.shared::cta;" ::: "memory");
                __syncwarp();
                e_arrive(bars + UB_STAGED);
            }
            if (k == PP_K && t + 1 < t1 && (pp || t == t0)) bar_arrive(11 - wg, 256);
            if (k == 5) fr = ld_rlx1(fl + F_P + (min(red_next + (lane & 1) * 2, NT64 - 1) * 4 + (p0 & 3)));
            if (k > 0) {
                wg_wait<1>();
                e_arrive(empty + ((k - 1) & 3) * 8);
                if (t + 2 >= t1) e_arrive(sb + U_BAR + UB_WFREE + (k - 1) * 8);
            }
        }
        wg_wait<0>();
        pin(acc);
        e_arrive(empty + 24);
        if (t + 2 >= t1) e_arrive(sb + U_BAR + UB_WFREE + 56);

        uint32_t pk[32];
        if (J == J_BQ || J == J_BKV) {
#pragma unroll
            for (int i = 0; i < 32; i++) acc[i] = phi(acc[i]);
        }
        if (J == J_BQ) {
            const int r0 = t * 64 + w4 * 16 + (lane >> 2);
            const float g0 = 1.f - gG[r0], g1 = 1.f - gG[r0 + 8];
#pragma unroll
            for (int i = 32; i < 64; i++) acc[i] = phi(acc[i]);
#pragma unroll
            for (int h = 0; h < 8; h++) {
                float* a = acc + 8 * h;
                const float2 za = lds64f(sb + U_Z + h * 64 + (lane & 3) * 8), zb = lds64f(sb + U_Z + h * 64 + 32 + (lane & 3) * 8);
                float d0 = (a[0] * za.x + a[1] * za.y) + (a[4] * zb.x + a[5] * zb.y), d1 = (a[2] * za.x + a[3] * za.y) + (a[6] * zb.x + a[7] * zb.y);
                d0 += __shfl_xor_sync(~0u, d0, 1); d1 += __shfl_xor_sync(~0u, d1, 1);
                d0 += __shfl_xor_sync(~0u, d0, 2); d1 += __shfl_xor_sync(~0u, d1, 2);
                d0 = g0 * rcp(d0 + 1e-6f); d1 = g1 * rcp(d1 + 1e-6f);
                a[0] *= d0; a[1] *= d0; a[2] *= d1; a[3] *= d1; a[4] *= d0; a[5] *= d0; a[6] *= d1; a[7] *= d1;
            }
        }
#pragma unroll
        for (int i = 0; i < 32; i++) pk[i] = pack_bf(acc[2 * i], acc[2 * i + 1]);
        if (J == J_QA) {
            const int seg = w4 >> 1;
            float sc[40];
            mbar_wait(full, round & 1); mbar_wait(full + 8, round & 1);
            wg_fence();
#pragma unroll
            for (int q = 0; q < 8; q++)
                wg_rs80(sc, pk[4 * q], pk[4 * q + 1], pk[4 * q + 2], pk[4 * q + 3], mk_desc(ring + (q >> 2) * U_STAGE, 16) + (q & 3) * 2, q);
            wg_commit();
            int r0 = (w4 & 1) * 16 + (lane >> 2);
            asm volatile("" : "+r"(r0) :: "memory");
            const float g0 = gG[t * 64 + seg * 32 + r0], g1 = gG[t * 64 + seg * 32 + r0 + 8];
            wg_wait<0>();
            pin(sc);
            e_arrive(empty); e_arrive(empty + 8);
            float p[20];
#pragma unroll
            for (int i = 0; i < 16; i++) {
                const float v = seg ? sc[16 + i] : sc[i];
                p[i] = ((i >> 2) * 8 + (lane & 3) * 2 + (i & 1) <= r0 + (i & 2) * 4) ? v : -INFINITY;
            }
#pragma unroll
            for (int i = 0; i < 4; i++) p[16 + i] = seg ? sc[36 + i] : sc[32 + i];
            float m0 = fmaxf(p[0], p[1]), m1 = fmaxf(p[2], p[3]);
#pragma unroll
            for (int j = 1; j < 5; j++) { m0 = fmaxf(m0, fmaxf(p[4 * j], p[4 * j + 1])); m1 = fmaxf(m1, fmaxf(p[4 * j + 2], p[4 * j + 3])); }
            m0 = fmaxf(m0, __shfl_xor_sync(~0u, m0, 1)); m1 = fmaxf(m1, __shfl_xor_sync(~0u, m1, 1));
            m0 = fmaxf(m0, __shfl_xor_sync(~0u, m0, 2)) * SCORE_C; m1 = fmaxf(m1, __shfl_xor_sync(~0u, m1, 2)) * SCORE_C;
            float l0 = 0.f, l1 = 0.f;
#pragma unroll
            for (int i = 0; i < 20; i++) {
                p[i] = ex2(fmaf(p[i], SCORE_C, (i & 2) ? -m1 : -m0));
                if (i & 2) l1 += p[i]; else l0 += p[i];
            }
            uint32_t pa[20];
#pragma unroll
            for (int i = 0; i < 8; i++) { const uint32_t w = pack_bf(p[2 * i], p[2 * i + 1]); pa[i] = seg ? 0 : w; pa[8 + i] = seg ? w : 0; }
#pragma unroll
            for (int i = 0; i < 2; i++) { const uint32_t w = pack_bf(p[16 + 2 * i], p[17 + 2 * i]); pa[16 + i] = seg ? 0 : w; pa[18 + i] = seg ? w : 0; }
            float o0[32], o1[32];
            mbar_wait(full + 16, round & 1); mbar_wait(full + 24, round & 1);
            wg_fence();
#pragma unroll
            for (int q = 0; q < 5; q++) {
                wg_rs64t(o0, pa[4 * q], pa[4 * q + 1], pa[4 * q + 2], pa[4 * q + 3], mk_desc(ring + 2 * U_STAGE, 16) + q * 128, q);
                wg_rs64t(o1, pa[4 * q], pa[4 * q + 1], pa[4 * q + 2], pa[4 * q + 3], mk_desc(ring + 3 * U_STAGE, 16) + q * 128, q);
            }
            wg_commit();
            l0 += __shfl_xor_sync(~0u, l0, 1); l1 += __shfl_xor_sync(~0u, l1, 1);
            l0 += __shfl_xor_sync(~0u, l0, 2); l1 += __shfl_xor_sync(~0u, l1, 2);
            const float i0 = g0 * rcp(l0), i1 = g1 * rcp(l1);
            wg_wait<0>();
            pin(o0); pin(o1);
            e_arrive(empty + 16); e_arrive(empty + 24);
#pragma unroll
            for (int i = 0; i < 16; i++) {
                const float f = (i & 1) ? i1 : i0;
                pk[i] = pack_bf(o0[2 * i] * f, o0[2 * i + 1] * f); pk[16 + i] = pack_bf(o1[2 * i] * f, o1[2 * i + 1] * f);
            }
            round++;
        }
        round += 2;
        if (J == J_BKV) bar_sync(8 + wg, 128);
        mbar_wait(bars + UB_FREE, (nout & 1) ^ 1);
        if (J == J_QA) {
            const uint32_t ob = sb + U_BAR + (wg ^ 1) * UB_WG + UB_FREE;
            if (t < 2) bar_sync(7 - wg, 256);
            mbar_wait(ob, ((nout + wg) & 1) ^ 1);
        }
        stage_half(stg0, lane, pk); stage_half(stg1, lane, pk + 16);
        held = DEFER && J != J_BKV && J != J_F && t >= 2 && t + 2 < t1;
        if (!held) asm volatile("fence.proxy.async.shared::cta;" ::: "memory");
        if (J == J_BKV) {
#pragma unroll
            for (int i = 0; i < 16; i++) { zs[(i >> 1) * 2] += bf_lo(pk[i]); zs[(i >> 1) * 2 + 1] += bf_hi(pk[i]); }
            bar_sync(8 + wg, 128);
            wg_fence();
#pragma unroll
            for (int q = 0; q < 4; q++) wg_ss64tt(kv, mk_desc(sb + U_STG + (wg * 4 + q) * 2048, 16), mk_desc(ring + q * U_STAGE + 8192, 16), 1);
            wg_commit();
            wg_wait<0>();
            pin(kv);
        } else {
            __syncwarp();
            if (!held) e_arrive(bars + UB_STAGED);
            nout++;
            const uint32_t done = __ballot_sync(~0u, fr >= 9);
            const bool last = t + 2 >= t1;
            const int lim = last ? NT64 : min(t, red_next + ((done & 1) ? ((done & 2) ? 4 : 2) : 0));
#pragma unroll 1
            for (; red_next < lim; red_next += 2) {
                if (last) wait_flag(fl + F_P + red_next * 4 + p0, 9);
                reduce_rows(out, lane, red_next, p0, job.p1 * 8 + w4 * 2);
            }
        }
        }
        TRACE(4 + J * 4);
        if (J == J_BKV) {
        float* dk = gKVp + (p0 + wg) * 1024 + w4 * 256 + (lane >> 2) * 16 + (lane & 3) * 2;
#pragma unroll
        for (int w = 0; w < 4; w++)
            if (w4 == w) {
                *reinterpret_cast<float2*>(dk) = make_float2(kv[8 * w], kv[8 * w + 1]);
                *reinterpret_cast<float2*>(dk + 128) = make_float2(kv[8 * w + 2], kv[8 * w + 3]);
                *reinterpret_cast<float2*>(dk + 8) = make_float2(kv[8 * w + 4], kv[8 * w + 5]);
                *reinterpret_cast<float2*>(dk + 136) = make_float2(kv[8 * w + 6], kv[8 * w + 7]);
            }
#pragma unroll
        for (int i = 0; i < 16; i++) {
            float z = zs[i];
            z += __shfl_xor_sync(~0u, z, 4); z += __shfl_xor_sync(~0u, z, 8); z += __shfl_xor_sync(~0u, z, 16);
            if (lane < 4) gZp[(p0 + wg) * 256 + w4 * 64 + (i >> 1) * 8 + lane * 2 + (i & 1)] = z;
        }
            bar_sync(8 + wg, 128);
            if (w4 == 0) e_red_rel(fl + F_B);
        }
    }
}

__device__ __forceinline__ void bulk_producer(const uint32_t sb, const unsigned epoch, const Maps& m, const int j, const int wg) {
    const int lane = threadIdx.x & 31;
    const uint32_t ring = sb + U_RING + wg * 4 * U_STAGE, bars = sb + U_BAR + wg * UB_WG;
    uint32_t round = 0, nout = 0, njob = 0;
#pragma unroll 1
    for (int J = first_job(j); J != J_END; J = next_job(J, j), njob++) {
        const Job job = job_of(J, j);
        int c0, d1, r0, ld;
        const bf16* raw;
        int wc0, wd1, wr0;
        const CUtensorMap* const wm = job_w(m, J, j, wc0, wd1, wr0, raw, ld);
        auto load_w = [&](int k) {
            const uint32_t bar = sb + U_BAR + UB_W + k * 8;
            mbar_wait(sb + U_BAR + UB_WFREE + k * 8, (njob + 1) & 1);
            e_expect(bar, 16384);
            e_tma2d(sb + U_W + k * 8192, wm, wc0, wr0 + k * 64, bar); e_tma2d(sb + U_W + 65536 + k * 8192, wm, wc0 + wd1, wr0 + k * 64, bar);
        };
        const bool w_first = J == J_F || J == J_BQ;
        if (wg == 0 && w_first) {
#pragma unroll 1
            for (int k = 0; k < 8; k++) load_w(k);
        }
        const int pft = min(job.t1 - job.t0, PF_T), pf0 = next_job(J, j) == J_END || !PF_T ? NT64 : job.t1 - pft, pfn = 128 / max(pft, 1);
        job_w(m, next_job(J, j), j, c0, d1, r0, raw, ld);
        unsigned* const fl = gFlags + (J != J_KV && J != J_BKV ? __shfl_sync(~0u, epoch, 0) & 1 : 0) * F_END;
#pragma unroll 1
        for (int t = job.t0 + wg; t < job.t1; t += 2) {
            if (J == J_F) wait_flag(fl + F_O + t * 16 + job.p1, 4);
            bool mem_ok = false;
            if (J == J_QA) {
                const uint32_t fv = ld_acq(lane == 0 ? fl + F_KV + job.p0 * NT64 + t : fl + F_M + job.p0 * NSEG + 2 * t + (lane & 1));
                if (__shfl_sync(~0u, fv, 0) < 2) wait_flag(fl + F_KV + job.p0 * NT64 + t, 2);
                mem_ok = __all_sync(~0u, lane == 0 || fv >= 4);
#pragma unroll
                for (int i = 0; i < 8; i++)
                    pf_line((i & 4 ? gV : gK) + (size_t)((2 * t + ((i >> 1) & 1)) * NH + job.p0) * 4096 + ((i & 1) * 32 + lane) * 64);
                if (mem_ok) {
#pragma unroll
                    for (int i = 0; i < 2; i++) pf_line((i ? gVm : gKm) + (size_t)((2 * t + (lane >> 4)) * NH + job.p0) * 1024 + (lane & 15) * 64);
                }
            }
#pragma unroll 1
            for (int k = 0; k < 8; k++) {
                const uint32_t st = k & 3, bar = bars + UB_FULL + st * 8;
                if (t == job.t0 && !w_first) {
                    if (k < 4) load_w(k);
                    if (k == 4) {
#pragma unroll 1
                        for (int q = 4; q < 8; q++) load_w(q);
                    }
                }
                mbar_wait(bars + UB_EMPTY + st * 8, (round + (k >> 2) + 1) & 1);
                e_expect(bar, 8192);
                if (J == J_F) e_g2s(ring + st * U_STAGE, gA + (size_t)(t * NKB + job.p1 * 8 + k) * 4096, 8192, bar);
                else e_tma2d(ring + st * U_STAGE, &m.x, k * 64, t * 64, bar);
                const int i = ((t - pf0) * 8 + k) * pfn + lane;
                if (t >= pf0 && lane < pfn) pf_line(raw + (size_t)(r0 + (i >> 1)) * ld + c0 + (i & 1) * d1);
            }
            round += 2;
            if (J == J_QA) {
#pragma unroll 1
                for (int pass = 0; pass < (mem_ok ? 1 : 2); pass++) {
                    if (pass) wait_flag(fl + F_M + job.p0 * NSEG + 2 * t + (lane & 1), 4);
#pragma unroll 1
                    for (int k = 0; k < 4; k++) {
                        const uint32_t dst = ring + k * U_STAGE, bar = bars + UB_FULL + k * 8;
                        if (!pass) {
                            const bf16* src = (k & 2 ? gV : gK) + (size_t)(2 * t * NH + job.p0) * 4096 + (k & 1) * 2048;
                            mbar_wait(bars + UB_EMPTY + k * 8, (round + 1) & 1);
                            if (t < 2) mbar_wait(bars + UB_FREE, (nout & 1) ^ 1);
                            e_expect(bar, 10240);
                            e_g2s(dst, src, 4096, bar); e_g2s(dst + 4096, src + NH * 4096, 4096, bar);
                        }
                        if (pass || mem_ok) {
                            const bf16* sm = (k & 2 ? gVm : gKm) + (size_t)(2 * t * NH + job.p0) * 1024 + (k & 1) * 512;
                            e_g2s(dst + 8192, sm, 1024, bar); e_g2s(dst + 9216, sm + NH * 1024, 1024, bar);
                        }
                    }
                }
                round++;
            }
            if (J != J_BKV) nout++;
        }
    }
}

__device__ __forceinline__ void bulk_writer(const uint32_t sb, unsigned* const fl, const int j, const int wg) {
    const uint32_t ring = sb + U_RING + wg * 4 * U_STAGE, bars = sb + U_BAR + wg * UB_WG;
    uint32_t nout = 0;
#pragma unroll 1
    for (int J = first_job(j); J != J_END; J = next_job(J, j)) {
        if (J == J_BKV) continue;
        const Job job = job_of(J, j);
        const int p0 = job.p0, p1 = job.p1;
#pragma unroll 1
        for (int t = job.t0 + wg; t < job.t1; t += 2) {
            unsigned char* d0;
            uint32_t hs = 8192, ws = 4096;
            int flag;
            if (J == J_KV) {
                d0 = reinterpret_cast<unsigned char*>(p1 ? gV : gK) + (size_t)(2 * t * NH + p0) * 8192;
                hs = 4096; ws = NH * 8192; flag = F_KV + p0 * NT64 + t;
            } else if (J == J_F) {
                d0 = reinterpret_cast<unsigned char*>(gP) + (size_t)((p1 * NT64 + t) * 4 + p0) * 16384;
                flag = F_P + t * 4 + p0;
            } else {
                d0 = reinterpret_cast<unsigned char*>(gA) + (size_t)(t * NKB + (J == J_BQ ? 64 : 0) + 2 * p0) * 8192;
                flag = F_O + t * 16 + (J == J_BQ ? 8 : p0 >> 2);
            }
            mbar_wait(bars + UB_STAGED, nout & 1);
            const bool paced = t >= 4 && t + 2 < NT64;
#pragma unroll 1
            for (int i = 0; i < 8; i++) {
                if (paced && i == (J == J_QA ? QA_GATE : 0)) quiet_window(fl);
                const int w = i & 3, h = (i >> 2) ^ 1;
                const uint32_t src = !h ? sb + U_STG + (wg * 4 + w) * 2048 : J == J_QA ? sb + U_STG + ((wg ^ 1) * 4 + w) * 2048 : ring + w * U_STAGE + 8192;
                e_s2g(d0 + h * hs + (w >> 1) * ws + (w & 1) * 2048, src, 2048);
            }
            asm volatile("cp.async.bulk.commit_group;" ::: "memory");
            asm volatile("cp.async.bulk.wait_group.read 0;" ::: "memory");
            e_arrive(bars + UB_FREE);
            asm volatile("cp.async.bulk.wait_group 0;" ::: "memory");
            e_red(fl + flag);
            nout++;
        }
    }
}

__device__ __forceinline__ void init_gate(const uint32_t sb, const bf16* __restrict__ x, const bf16* __restrict__ gw, const int j) {
    const int lane = threadIdx.x & 31;
#pragma unroll 1
    for (int warp = (threadIdx.x >> 5) & 3; warp < 8; warp += 4) {
    uint4 xv[8];
    {
        const unsigned char* xs = reinterpret_cast<const unsigned char*>(x + (size_t)(j * SEG + warp * 4) * DM) + lane * 16;
#pragma unroll
        for (int i = 0; i < 8; i++) xv[i] = ld_rlx4(xs + i * 512);
    }
    const uint4 w0 = ld_rlx4(gw + lane * 8), w1 = ld_rlx4(gw + lane * 8 + 256);
    uint32_t xmax = 0;
    {
        float d[4];
#pragma unroll
        for (int r = 0; r < 4; r++) {
            const uint4 a = xv[2 * r], b = xv[2 * r + 1];
            xmax = __vmaxu2(xmax, __vmaxu2(absmax8(a), absmax8(b)));
            d[r] = (bf_lo(a.x) * bf_lo(w0.x) + bf_hi(a.x) * bf_hi(w0.x)) + (bf_lo(a.y) * bf_lo(w0.y) + bf_hi(a.y) * bf_hi(w0.y))
                 + (bf_lo(a.z) * bf_lo(w0.z) + bf_hi(a.z) * bf_hi(w0.z)) + (bf_lo(a.w) * bf_lo(w0.w) + bf_hi(a.w) * bf_hi(w0.w))
                 + (bf_lo(b.x) * bf_lo(w1.x) + bf_hi(b.x) * bf_hi(w1.x)) + (bf_lo(b.y) * bf_lo(w1.y) + bf_hi(b.y) * bf_hi(w1.y))
                 + (bf_lo(b.z) * bf_lo(w1.z) + bf_hi(b.z) * bf_hi(w1.z)) + (bf_lo(b.w) * bf_lo(w1.w) + bf_hi(b.w) * bf_hi(w1.w));
        }
#pragma unroll 1
        for (int o = 16; o; o >>= 1) {
#pragma unroll
            for (int r = 0; r < 4; r++) d[r] += __shfl_xor_sync(~0u, d[r], o);
        }
        if (lane < 4) gG[j * SEG + warp * 4 + lane] = __fdividef(1.f, 1.f + __expf(-(lane == 0 ? d[0] : lane == 1 ? d[1] : lane == 2 ? d[2] : d[3])));
        xmax = __reduce_max_sync(~0u, max(xmax & 0xffffu, xmax >> 16)) << 16;
    }
    if (lane == 0) sts32(sb + U_Z + warp * 4, xmax);
    }
    bar_arrive(5, 160);
}
__device__ __forceinline__ void init_acc(unsigned* const fl, const bf16* __restrict__ mem0, unsigned char* __restrict__ acc, const int j) {
    const int lane = threadIdx.x & 31;
        const uint4* ms = reinterpret_cast<const uint4*>(mem0) + lane;
        uint32_t mm = 0;
#pragma unroll 4
        for (int i = 0; i < 16; i++) mm = __vmaxu2(mm, absmax8(ms[i * 32]));
#pragma unroll 1
        for (int i = 1 + lane / 10; i < NSEG; i += 3) if (lane < 30) st_rlx4(acc + acc_line(i, j) + (lane % 10) * 16, 0);
        if (lane < 16) st_rlx4(gTime + j * NREC + lane * 4, 0);
        mm = __reduce_max_sync(~0u, max(mm & 0xffffu, mm >> 16));
        const int e = min(max(141 - (int)(mm >> 7), -60), 60);
        const float up = __uint_as_float((127 + e) << 23);
        if (lane == 0 && j == 0) st_rlx1(fl + F_BAR + 1, e);
        {
            const int l = (j & 3) * 8 + (lane >> 2);
            const bf16* p = mem0 + (l & 3) * 2 * DM + (j >> 2) * 32 + (lane & 3) * 8 + (l >> 2);
            const uint32_t w = pack_h(__bfloat162float(p[0]) * up, __bfloat162float(p[DM]) * up);
            const bool last = (lane & 3) == 3;
            st_rlx1(acc + acc_line(0, j) + lane * 4, last ? (w & 0xffffu) | 0x50000000u : w);
            if (last) st_rlx1(acc + acc_line(0, j) + 128 + (lane >> 2) * 4, (w >> 16) | 0x50000000u);
        }
}

__global__ void __cluster_dims__(2, 1, 1) __launch_bounds__(384, 1)
bulk_kernel(const __grid_constant__ Maps m, const bf16* __restrict__ x, const bf16* __restrict__ mem0, const bf16* __restrict__ gw,
            unsigned char* __restrict__ acc, bf16* __restrict__ out) {
    extern __shared__ __align__(1024) unsigned char smem_raw[];
    const uint32_t sb = s2u(smem_raw);
    const int j = blockIdx.x, warp = fresh_warp();
    if (LORD == 1) asm volatile("griddepcontrol.launch_dependents;");
    TRACE(0);
    const unsigned epoch = ld_rlx1(&gEpoch);
    if (threadIdx.x == 0) {
#pragma unroll 1
        for (int w = 0; w < 2; w++) {
            const uint32_t b = sb + U_BAR + w * UB_WG;
#pragma unroll 1
            for (int i = 0; i < 4; i++) { mbar_init(b + UB_FULL + i * 8, 1); mbar_init(b + UB_EMPTY + i * 8, 4); }
            mbar_init(b + UB_STAGED, 4); mbar_init(b + UB_FREE, 1);
        }
#pragma unroll 1
        for (int i = 0; i < 8; i++) { mbar_init(sb + U_BAR + UB_W + i * 8, 1); mbar_init(sb + U_BAR + UB_WFREE + i * 8, 8); }
        asm volatile("fence.mbarrier_init.release.cluster;" ::: "memory");
    }
    __syncthreads();
    if (warp < 8) {
        asm volatile("setmaxnreg.inc.sync.aligned.u32 208;");
        if (j < NREC && warp >= 4) init_gate(sb, x, gw, j);
        bulk_consumer(sb, gFlags + (__shfl_sync(~0u, epoch, 0) & 1) * F_END, out, j);
    } else {
        asm volatile("setmaxnreg.dec.sync.aligned.u32 88;");
        if (warp < 10) bulk_producer(sb, epoch, m, j, warp - 8);
        else {
            const unsigned par = __shfl_sync(~0u, epoch, 0) & 1;
            unsigned* const fl = gFlags + par * F_END;
            if (j < NREC && warp == 11) {
                init_acc(fl, mem0, acc, j);
                {
                    for (int i = threadIdx.x & 31; i < F_END / NREC; i += 32) gFlags[(par ^ 1) * F_END + j * (F_END / NREC) + i] = 0;
                    bar_sync(5, 160);
                    const uint32_t xm = __reduce_max_sync(~0u, __float_as_uint(lds32f(sb + U_Z + (threadIdx.x & 7) * 4)));
                    st_rlx1(fl + F_X + j, xm);
                    __syncwarp();
                    e_red_rel(fl + F_BAR);
                }
            }
            bulk_writer(sb, fl, j, warp - 10);
            if (LORD == 0) asm volatile("griddepcontrol.wait;" ::: "memory");
            if (j == EPOCH_J && threadIdx.x == 320) gEpoch = epoch + 1;
        }
    }
}

typedef CUresult (*EncodeFn)(CUtensorMap*, CUtensorMapDataType, cuuint32_t, void*, const cuuint64_t*, const cuuint64_t*, const cuuint32_t*,
                             const cuuint32_t*, CUtensorMapInterleave, CUtensorMapSwizzle, CUtensorMapL2promotion, CUtensorMapFloatOOBfill);
static void make_map(EncodeFn enc, CUtensorMap* m, void* p, int rows, int cols, int box_rows, bool swz = true) {
    const cuuint64_t dim[2] = {(cuuint64_t)cols, (cuuint64_t)rows}, str[1] = {(cuuint64_t)cols * 2};
    const cuuint32_t box[2] = {64, (cuuint32_t)box_rows}, es[2] = {1, 1};
    enc(m, CU_TENSOR_MAP_DATA_TYPE_BFLOAT16, 2, p, dim, str, box, es, CU_TENSOR_MAP_INTERLEAVE_NONE,
        swz ? CU_TENSOR_MAP_SWIZZLE_128B : CU_TENSOR_MAP_SWIZZLE_NONE,
        CU_TENSOR_MAP_L2_PROMOTION_L2_128B, CU_TENSOR_MAP_FLOAT_OOB_FILL_NONE);
}

extern "C" void kernel_launch(void* const* d_in, const int* in_sizes, int n_in, void* d_out, int out_size) {
    void* fn = nullptr;
    cudaDriverEntryPointQueryResult qr;
    cudaGetDriverEntryPoint("cuTensorMapEncodeTiled", &fn, cudaEnableDefault, &qr);
    EncodeFn enc = (EncodeFn)fn;
    Maps m;
    make_map(enc, &m.x, d_in[0], NTOK, DM, 64);
    make_map(enc, &m.wq, d_in[2], DM, HD, 64);
    make_map(enc, &m.wk, d_in[3], DM, HD, 64);
    make_map(enc, &m.wv, d_in[4], DM, HD, 64);
    make_map(enc, &m.wo, d_in[5], HD, DM, 64);
    make_map(enc, &m.wb, d_in[8], DM, 3 * DM, 64);
    make_map(enc, &m.wo2, d_in[9], DM, DM, 64);
    m.pq = (const bf16*)d_in[2]; m.pk = (const bf16*)d_in[3]; m.pv = (const bf16*)d_in[4]; m.po = (const bf16*)d_in[5];
    m.pb = (const bf16*)d_in[8]; m.po2 = (const bf16*)d_in[9];
    void* pA;
    cudaGetSymbolAddress(&pA, gAccRaw);
    unsigned char* acc = (unsigned char*)(((uintptr_t)pA + 0xfffff) & ~(uintptr_t)0xfffff);
    cudaFuncSetAttribute(rec_kernel, cudaFuncAttributeMaxDynamicSharedMemorySize, R_END);
    cudaFuncSetAttribute(bulk_kernel, cudaFuncAttributeMaxDynamicSharedMemorySize, U_END);
    cudaLaunchAttribute at[1];
    at[0].id = cudaLaunchAttributeProgrammaticStreamSerialization; at[0].val.programmaticStreamSerializationAllowed = 1;
    cudaLaunchConfig_t cr = {}, cb = {};
    cr.gridDim = dim3(NREC); cr.blockDim = dim3(256); cr.dynamicSmemBytes = R_END; cr.stream = cudaStreamPerThread; cr.attrs = at;
    cb.gridDim = dim3(68); cb.blockDim = dim3(384); cb.dynamicSmemBytes = U_END; cb.stream = cudaStreamPerThread; cb.attrs = at;
    static cudaStream_t s2 = nullptr;
    static cudaEvent_t ef, ej;
    if (!s2) { cudaStreamCreateWithFlags(&s2, cudaStreamNonBlocking); cudaEventCreateWithFlags(&ef, cudaEventDisableTiming); cudaEventCreateWithFlags(&ej, cudaEventDisableTiming); }
    cr.stream = s2;
    cudaEventRecord(ef, cudaStreamPerThread); cudaStreamWaitEvent(s2, ef, 0);
    cudaLaunchKernelEx(&cb, bulk_kernel, m, (const bf16*)d_in[0], (const bf16*)d_in[1], (const bf16*)d_in[10], acc, (bf16*)d_out);
    cudaLaunchKernelEx(&cr, rec_kernel, m, acc, 0u);
    cudaEventRecord(ej, s2); cudaStreamWaitEvent(cudaStreamPerThread, ej, 0);
}
```
